```python
import torch

def _softmax(x, axis=-1):
    return torch.softmax(x, dim=axis)

def _gelu(x):
    return torch.nn.functional.gelu(x, approximate='tanh')

def _silu(x):
    return torch.nn.functional.silu(x)

def _sigmoid(x):
    return torch.sigmoid(x)

def _layernorm(x, axis=-1, eps=1e-05):
    m = x.mean(dim=axis, keepdim=True)
    v = x.var(dim=axis, keepdim=True, unbiased=False)
    return (x - m) / torch.sqrt(v + eps)

def _scatter_add(tgt, idx, src, axis=0):
    return tgt.clone().index_add_(axis, idx, src)

def _segment_sum(src, seg, n):
    out = torch.zeros((n,) + src.shape[1:], dtype=src.dtype)
    return out.index_add_(0, seg, src)

def _pad(x, pw):
    flat = tuple((v for pair in reversed(pw) for v in pair))
    return torch.nn.functional.pad(x, flat)
kernel_name = 'adaLN_cond__ssm_conv_s4__mixer_s_mlp__prompt'

def setup_inputs():

    _w = lambda a: (lambda t: t.to(torch.bfloat16) if t.is_floating_point() else t)(torch.as_tensor(a))

    def _A_setup():
        B, L, D, N = (1, 2048, 512, 128)
        A_re = -(lambda _x: torch.exp(torch.as_tensor(_x)))((lambda *s: torch.randn(*s, dtype=torch.bfloat16) * 3.2)(D, N))
        A_im = torch.pi * (lambda *s: torch.randn(*s, dtype=torch.bfloat16) * 0.1)(D, N)
        B_re = (lambda *s: torch.randn(*s, dtype=torch.bfloat16) * 0.2)(D, N)
        B_im = (lambda *s: torch.randn(*s, dtype=torch.bfloat16) * 0.2)(D, N)
        C_re = (lambda *s: torch.randn(*s, dtype=torch.bfloat16) * 0.2)(D, N)
        C_im = (lambda *s: torch.randn(*s, dtype=torch.bfloat16) * 0.2)(D, N)
        log_dt = (lambda *s: torch.randn(*s, dtype=torch.bfloat16) * 0.1)(D) * 0.5 - 4.0
        Dskip = (lambda *s: torch.randn(*s, dtype=torch.bfloat16) * 0.1)(D)
        return {'u': _w((lambda *s: torch.randn(*s, dtype=torch.bfloat16) * 0.05)(B, L, D)), 'A_re': _w(A_re), 'A_im': _w(A_im), 'B_re': _w(B_re), 'B_im': _w(B_im), 'C_re': _w(C_re), 'C_im': _w(C_im), 'log_dt': _w(log_dt), 'Dskip': _w(Dskip)}
    _A_in = _A_setup()

    def _B_setup():
        B, S, D, F = (1, 2048, 512, 1792)
        return {'x': _w((lambda *s: torch.randn(*s, dtype=torch.bfloat16) * 0.05)(B, S, D)), 'w1': _w((lambda *s: torch.randn(*s, dtype=torch.bfloat16) * 3.2)(D, D) * D ** (-0.5)), 'w2': _w((lambda *s: torch.randn(*s, dtype=torch.bfloat16) * 3.2)(D, D) * D ** (-0.5)), 'w3': _w((lambda *s: torch.randn(*s, dtype=torch.bfloat16) * 3.2)(D, F) * D ** (-0.5)), 'w4': _w((lambda *s: torch.randn(*s, dtype=torch.bfloat16) * 1.6)(F, D) * F ** (-0.5))}
    _B_in = _B_setup()
    return {'A_u': _A_in['u'], 'A_A_re': _A_in['A_re'], 'A_A_im': _A_in['A_im'], 'A_B_re': _A_in['B_re'], 'A_B_im': _A_in['B_im'], 'A_C_re': _A_in['C_re'], 'A_C_im': _A_in['C_im'], 'A_log_dt': _A_in['log_dt'], 'A_Dskip': _A_in['Dskip'], 'B_x': _B_in['x'], 'B_w1': _B_in['w1'], 'B_w2': _B_in['w2'], 'B_w3': _B_in['w3'], 'B_w4': _B_in['w4'], 'c': _w((lambda *s: torch.randn(*s, dtype=torch.bfloat16) * 0.1)(1, 512) * 8.0), 'w_mod': _w((lambda *s: torch.randn(*s, dtype=torch.bfloat16) * 0.1)(512, 6 * 512) * 512 ** (-0.5) * 8.0)}

def reference(A_u, A_A_re, A_A_im, A_B_re, A_B_im, A_C_re, A_C_im, A_log_dt, A_Dskip, B_x, B_w1, B_w2, B_w3, B_w4, c, w_mod):

    def _A_ref(u, A_re, A_im, B_re, B_im, C_re, C_im, log_dt, Dskip):
        Bsz, L, D = u.shape
        dt = torch.exp(log_dt)[:, None]
        A = A_re + 1j * A_im
        Bc = B_re + 1j * B_im
        Cc = C_re + 1j * C_im
        logdA = dt * A
        dB = dt * Bc
        l = (lambda x, dt: x.to(dt))(torch.arange(L), A_re.dtype)
        P = torch.exp(logdA[:, :, None] * l[None, None, :])
        K = torch.einsum('dn,dnl,dn->dl', Cc, P, dB).real
        L2 = 2 * L
        Kp = _pad(K, ((0, 0), (0, L)))
        up = (lambda x, *d: x.permute(*d))(u, 0, 2, 1)
        up = _pad(up, ((0, 0), (0, 0), (0, L)))
        Kf = (lambda x, axes=(-2, -1): torch.fft.rfft2(x.float(), dim=axes))(Kp[:, None, :], axes=(-2, -1))
        Uf = (lambda x, axes=(-2, -1): torch.fft.rfft2(x.float(), dim=axes))(up[:, :, None, :], axes=(-2, -1))
        Yf = Uf * Kf[None, :, :, :]
        y = (lambda x, s, axes=(-2, -1): torch.fft.irfft2(x, s=s, dim=axes).to(torch.bfloat16))(Yf, (1, L2), axes=(-2, -1))[:, :, 0, :L]
        y = (lambda x, *d: x.permute(*d))(y, 0, 2, 1) + u * Dskip[None, None, :]
        return y

    def _B_ref(x, w1, w2, w3, w4):
        B, S, D = x.shape
        h = _gelu(_layernorm(x, axis=-1) @ w1)
        c = D // 4
        g0 = _pad(h[:, :, 0 * c:1 * c], ((0, 0), (1, 0), (0, 0)))[:, :S, :]
        g1 = _pad(h[:, :, 1 * c:2 * c], ((0, 0), (0, 1), (0, 0)))[:, 1:, :]
        g2 = _pad(h[:, :, 2 * c:3 * c], ((0, 0), (2, 0), (0, 0)))[:, :S, :]
        g3 = _pad(h[:, :, 3 * c:], ((0, 0), (0, 2), (0, 0)))[:, 2:, :]
        hs = torch.concatenate([g0, g1, g2, g3], axis=-1) @ w2
        x1 = x + hs
        h2 = _gelu(_layernorm(x1, axis=-1) @ w3) @ w4
        return x1 + h2
    x = A_u
    mod = (_silu(c) @ w_mod).reshape(c.shape[0], 6, 1, -1)
    sa, ca, ga, sb, cb, gb = (mod[:, 0].clone(), mod[:, 1].clone(), mod[:, 2].clone(), mod[:, 3].clone(), mod[:, 4].clone(), mod[:, 5].clone())
    h = _layernorm(x, axis=-1) * (1 + ca) + sa
    x = x + ga * _A_ref(h, A_A_re, A_A_im, A_B_re, A_B_im, A_C_re, A_C_im, A_log_dt, A_Dskip)
    h = _layernorm(x, axis=-1) * (1 + cb) + sb
    x = x + gb * _B_ref(h, B_w1, B_w2, B_w3, B_w4)
    return x
```

```cpp
#include <cuda_runtime.h>
#include <cuda_bf16.h>
#include <cuda.h>
#include <stdint.h>

namespace {

typedef __nv_bfloat16 bf16;

constexpr int SM_W1 = 0, SM_W2 = 65536, SM_Q = 131072, NSLOT = 11, SM_MISC = SM_Q + NSLOT * 8192;
constexpr int UW_B = 10912, SM_UW = SM_W2, XS_B = 10240, SM_XS = SM_UW + 4 * UW_B;
constexpr int WD_B = 3104, SM_WD = SM_Q, SM_FAR = SM_Q + 8 * 8192;
constexpr int QP_PITCH = 528, QP_B = 56 * QP_PITCH;
constexpr int SM_BAR = SM_MISC;
constexpr int SM_CS = SM_BAR + 1280;
constexpr int SM_U123 = SM_CS + 4096;
constexpr int SM_GB = SM_U123 + 768;
constexpr int SM_U4 = SM_GB + 256;
constexpr int SM_RED = SM_U4 + 896;
constexpr int SM_ARED = SM_RED + 1536;
constexpr int SM_OWN = SM_ARED + 512;
constexpr int SM_CONST = SM_OWN + 64;
constexpr int SM_TOTAL = SM_CONST + 64;
static_assert(SM_XS + 2 * XS_B <= SM_Q, "conv buffers");
static_assert(SM_TOTAL <= 232448, "smem");
constexpr int T0o = 8, T4o = 288, T2o = 432, TM2o = 512, T1o = 592, T3o = 640, T5o = 688, TM1o = 736;
constexpr int B_FULL = 0, B_EMPTY = 48, B_WFULL = 96, B_WEMPTY = 112, B_W1FULL = 128, B_W2FULL = 129, B_W1SC = 130,
              B_CONV = 131  , B_W1FREE = 133, B_W2FREE = 134, B_MOD = 135  , B_HFREE = 137  ,
              B_HFULL = 139  , B_UREADY = 141, B_SEEN = 142, B_FAR = 143  , B_COUNT = 155;

constexpr float LN_EPS = 1e-5f;
constexpr uint32_t SENT = 0xFFFFFFFFu;
constexpr int SPIN_MAX = 1 << 20;

__device__ uint2 g_stats0[2048];
__device__ uint32_t g_modp[3 * 256];
__device__ uint32_t g_u123[3 * 512];
__device__ uint32_t g_u4[1792];
__device__ uint4 g_stats1[2048];
__device__ float2 g_stats2[2048 * 8];
__device__ __align__(1024) bf16 g_x2t[512 * 2048];
__device__ __align__(1024) bf16 g_g[2048 * 512];
__device__ __align__(1024) bf16 g_x1[2048 * 512];
__device__ uint4 g_part[16 * 8 * 3 * 2 * 512];
__device__ uint32_t g_cnt[2 * 8 * 32];
__device__ uint32_t g_flag[2 * 32 * 8 * 32];
__device__ uint32_t g_epoch[128];

struct Params {
    const bf16 *x, *Are, *Aim, *Bre, *Bim, *Cre, *Cim, *logdt, *dskip, *w1, *w2, *w3, *w4, *c, *wmod;
    bf16* out;
};

__device__ __forceinline__ void mbar_init(uint32_t b, int c) { asm volatile("mbarrier.init.shared::cta.b64 [%0], %1;" ::"r"(b), "r"(c) : "memory"); }
__device__ __forceinline__ void mbar_expect(uint32_t b, int bytes) { asm volatile("mbarrier.arrive.expect_tx.shared::cta.b64 _, [%0], %1;" ::"r"(b), "r"(bytes) : "memory"); }
__device__ __forceinline__ void mbar_arrive(uint32_t b) { asm volatile("mbarrier.arrive.shared::cta.b64 _, [%0];" ::"r"(b) : "memory"); }
__device__ __forceinline__ void mbar_arrive_remote(uint32_t b) { asm volatile("mbarrier.arrive.release.cluster.shared::cluster.b64 _, [%0];" ::"r"(b) : "memory"); }
__device__ __forceinline__ void mbar_wait(uint32_t b) {
    uint32_t ok; int it = 0;
    do {
        asm volatile("{.reg .pred p; mbarrier.try_wait.parity.shared::cta.b64 p, [%1], 0; selp.u32 %0, 1, 0, p;}" : "=r"(ok) : "r"(b) : "memory");
        if (!ok && ++it > SPIN_MAX) __trap();
    } while (!ok);
}
__device__ __forceinline__ void mbar_wait_cluster(uint32_t b) {
    uint32_t ok; int it = 0;
    do {
        asm volatile("{.reg .pred p; mbarrier.try_wait.parity.acquire.cluster.shared::cta.b64 p, [%1], 0; selp.u32 %0, 1, 0, p;}" : "=r"(ok) : "r"(b) : "memory");
        if (!ok && ++it > SPIN_MAX) __trap();
    } while (!ok);
}
__device__ __forceinline__ void warp_arrive(uint32_t b) { __syncwarp(); if ((threadIdx.x & 31) == 0) mbar_arrive(b); }
__device__ __forceinline__ void bar_sync(int id, int n) { asm volatile("bar.sync %0, %1;" ::"r"(id), "r"(n) : "memory"); }
__device__ __forceinline__ void fence_async_smem() { asm volatile("fence.proxy.async.shared::cta;" ::: "memory"); }
__device__ __forceinline__ void fence_async_all() { asm volatile("fence.proxy.async;" ::: "memory"); }
__device__ __forceinline__ uint32_t mapa(uint32_t a, uint32_t r) { uint32_t d; asm("mapa.shared::cluster.u32 %0, %1, %2;" : "=r"(d) : "r"(a), "r"(r)); return d; }

__device__ __forceinline__ void tma2d(uint32_t dst, const CUtensorMap* m, int c0, int c1, uint32_t bar) {
    asm volatile("cp.async.bulk.tensor.2d.shared::cluster.global.mbarrier::complete_tx::bytes [%0], [%1, {%3, %4}], [%2];"
                 ::"r"(dst), "l"(m), "r"(bar), "r"(c0), "r"(c1) : "memory");
}
__device__ __forceinline__ void tma5d(uint32_t dst, const CUtensorMap* m, int c0, int c1, int c2, int c3, int c4, uint32_t bar) {
    asm volatile("cp.async.bulk.tensor.5d.shared::cluster.global.mbarrier::complete_tx::bytes [%0], [%1, {%3, %4, %5, %6, %7}], [%2];"
                 ::"r"(dst), "l"(m), "r"(bar), "r"(c0), "r"(c1), "r"(c2), "r"(c3), "r"(c4) : "memory");
}
__device__ __forceinline__ void l2_prefetch(const void* p, int bytes) { asm volatile("cp.async.bulk.prefetch.L2.global [%0], %1;" ::"l"(p), "r"(bytes) : "memory"); }

__device__ __forceinline__ uint32_t lds32(uint32_t a) { uint32_t v; asm volatile("ld.shared.b32 %0, [%1];" : "=r"(v) : "r"(a)); return v; }
__device__ __forceinline__ uint2 lds64(uint32_t a) { uint2 v; asm volatile("ld.shared.v2.b32 {%0,%1}, [%2];" : "=r"(v.x), "=r"(v.y) : "r"(a)); return v; }
__device__ __forceinline__ uint4 lds128(uint32_t a) { uint4 v; asm volatile("ld.shared.v4.b32 {%0,%1,%2,%3}, [%4];" : "=r"(v.x), "=r"(v.y), "=r"(v.z), "=r"(v.w) : "r"(a)); return v; }
__device__ __forceinline__ float ldsf(uint32_t a) { return __uint_as_float(lds32(a)); }
__device__ __forceinline__ float2 ldsf2(uint32_t a) { uint2 v = lds64(a); return make_float2(__uint_as_float(v.x), __uint_as_float(v.y)); }
__device__ __forceinline__ void sts16(uint32_t a, uint32_t v) { asm volatile("st.shared.b16 [%0], %1;" ::"r"(a), "h"((unsigned short)v) : "memory"); }
__device__ __forceinline__ void sts32(uint32_t a, uint32_t v) { asm volatile("st.shared.b32 [%0], %1;" ::"r"(a), "r"(v) : "memory"); }
__device__ __forceinline__ void stsf(uint32_t a, float v) { sts32(a, __float_as_uint(v)); }
__device__ __forceinline__ void sts64(uint32_t a, uint32_t x, uint32_t y) { asm volatile("st.shared.v2.b32 [%0], {%1,%2};" ::"r"(a), "r"(x), "r"(y) : "memory"); }
__device__ __forceinline__ void sts128(uint32_t a, uint4 v) { asm volatile("st.shared.v4.b32 [%0], {%1,%2,%3,%4};" ::"r"(a), "r"(v.x), "r"(v.y), "r"(v.z), "r"(v.w) : "memory"); }
__device__ __forceinline__ void ldsm4(uint32_t* r, uint32_t a) { asm volatile("ldmatrix.sync.aligned.m8n8.x4.shared.b16 {%0,%1,%2,%3}, [%4];" : "=r"(r[0]), "=r"(r[1]), "=r"(r[2]), "=r"(r[3]) : "r"(a)); }
__device__ __forceinline__ void ldsm4t(uint32_t* r, uint32_t a) { asm volatile("ldmatrix.sync.aligned.m8n8.x4.trans.shared.b16 {%0,%1,%2,%3}, [%4];" : "=r"(r[0]), "=r"(r[1]), "=r"(r[2]), "=r"(r[3]) : "r"(a)); }
__device__ __forceinline__ void stsm4(uint32_t a, uint32_t r0, uint32_t r1, uint32_t r2, uint32_t r3) { asm volatile("stmatrix.sync.aligned.m8n8.x4.shared.b16 [%0], {%1,%2,%3,%4};" ::"r"(a), "r"(r0), "r"(r1), "r"(r2), "r"(r3) : "memory"); }

__device__ __forceinline__ uint32_t ldg32(const void* p) { uint32_t v; asm volatile("ld.global.nc.b32 %0, [%1];" : "=r"(v) : "l"(p)); return v; }
__device__ __forceinline__ uint2 ldg64(const void* p) { uint2 v; asm volatile("ld.global.nc.L1::no_allocate.v2.b32 {%0,%1}, [%2];" : "=r"(v.x), "=r"(v.y) : "l"(p)); return v; }
__device__ __forceinline__ uint4 ldg128(const void* p) { uint4 v; asm volatile("ld.global.nc.L1::no_allocate.v4.b32 {%0,%1,%2,%3}, [%4];" : "=r"(v.x), "=r"(v.y), "=r"(v.z), "=r"(v.w) : "l"(p)); return v; }
__device__ __forceinline__ uint32_t ldr32(const void* p) { uint32_t v; asm volatile("ld.relaxed.gpu.global.b32 %0, [%1];" : "=r"(v) : "l"(p) : "memory"); return v; }
__device__ __forceinline__ uint32_t lda32(const void* p) { uint32_t v; asm volatile("ld.acquire.gpu.global.b32 %0, [%1];" : "=r"(v) : "l"(p) : "memory"); return v; }
__device__ __forceinline__ uint2 ldr64(const void* p) { uint2 v; asm volatile("ld.relaxed.gpu.global.v2.b32 {%0,%1}, [%2];" : "=r"(v.x), "=r"(v.y) : "l"(p) : "memory"); return v; }
__device__ __forceinline__ uint4 ldr128(const void* p) { uint4 v; asm volatile("ld.relaxed.gpu.global.v4.b32 {%0,%1,%2,%3}, [%4];" : "=r"(v.x), "=r"(v.y), "=r"(v.z), "=r"(v.w) : "l"(p) : "memory"); return v; }
__device__ __forceinline__ void str32(void* p, uint32_t v) { asm volatile("st.relaxed.gpu.global.b32 [%0], %1;" ::"l"(p), "r"(v) : "memory"); }
__device__ __forceinline__ void str64(void* p, uint32_t x, uint32_t y) { asm volatile("st.relaxed.gpu.global.v2.b32 [%0], {%1,%2};" ::"l"(p), "r"(x), "r"(y) : "memory"); }
__device__ __forceinline__ void str128(void* p, uint4 v) { asm volatile("st.relaxed.gpu.global.v4.b32 [%0], {%1,%2,%3,%4};" ::"l"(p), "r"(v.x), "r"(v.y), "r"(v.z), "r"(v.w) : "memory"); }
__device__ __forceinline__ void stg32(void* p, uint32_t v) { asm volatile("st.global.b32 [%0], %1;" ::"l"(p), "r"(v) : "memory"); }
__device__ __forceinline__ void stg128(void* p, uint32_t x, uint32_t y, uint32_t z, uint32_t w) { asm volatile("st.global.v4.b32 [%0], {%1,%2,%3,%4};" ::"l"(p), "r"(x), "r"(y), "r"(z), "r"(w) : "memory"); }
__device__ __forceinline__ bool valid4(uint4 v) { return v.x != SENT && v.y != SENT && v.z != SENT && v.w != SENT; }

__device__ __forceinline__ uint32_t pack2(float lo, float hi) { uint32_t r; asm("cvt.rn.bf16x2.f32 %0, %1, %2;" : "=r"(r) : "f"(hi), "f"(lo)); return r; }
__device__ __forceinline__ float blo(uint32_t v) { return __uint_as_float(v << 16); }
__device__ __forceinline__ float bhi(uint32_t v) { return __uint_as_float(v & 0xFFFF0000u); }
__device__ __forceinline__ float bround(float v) { return blo(pack2(v, 0.f)); }
__device__ __forceinline__ uint32_t hadd2(uint32_t a, uint32_t b) { uint32_t r; asm("add.rn.bf16x2 %0, %1, %2;" : "=r"(r) : "r"(a), "r"(b)); return r; }
__device__ __forceinline__ uint32_t hmul2(uint32_t a, uint32_t b) { uint32_t r; asm("mul.rn.bf16x2 %0, %1, %2;" : "=r"(r) : "r"(a), "r"(b)); return r; }
__device__ __forceinline__ uint32_t prmt(uint32_t a, uint32_t b, uint32_t s) { uint32_t r; asm("prmt.b32 %0, %1, %2, %3;" : "=r"(r) : "r"(a), "r"(b), "r"(s)); return r; }
__device__ __forceinline__ float shx(float v, int m) { return __shfl_xor_sync(0xffffffffu, v, m); }
__device__ __forceinline__ float gelu(float x) {
    float t, u = x * fmaf(x * x, 0.0356774081363001f, 0.7978845608028654f);
    asm("tanh.approx.f32 %0, %1;" : "=f"(t) : "f"(u));
    float h = 0.5f * x;
    return fmaf(h, t, h);
}
template <int NV> __device__ __forceinline__ void halve(float* v, int mask, bool up) {
#pragma unroll
    for (int i = 0; i < NV / 2; i++) {
        float send = up ? v[i] : v[i + NV / 2], keep = up ? v[i + NV / 2] : v[i];
        v[i] = keep + shx(send, mask);
    }
}

struct cf { float x, y; };
__device__ __forceinline__ cf cmul(cf a, cf b) { cf r; r.x = fmaf(a.x, b.x, -a.y * b.y); r.y = fmaf(a.x, b.y, a.y * b.x); return r; }
__device__ __forceinline__ cf cexp2(float e, float th) {
    float m; asm("ex2.approx.ftz.f32 %0, %1;" : "=f"(m) : "f"(e));
    cf r; r.x = m * __cosf(th); r.y = m * __sinf(th); return r;
}

__device__ __forceinline__ void mma(float* d, uint32_t a0, uint32_t a1, uint32_t a2, uint32_t a3, uint32_t b0, uint32_t b1) {
    asm volatile("mma.sync.aligned.m16n8k16.row.col.f32.bf16.bf16.f32 {%0,%1,%2,%3},{%4,%5,%6,%7},{%8,%9},{%0,%1,%2,%3};"
                 : "+f"(d[0]), "+f"(d[1]), "+f"(d[2]), "+f"(d[3]) : "r"(a0), "r"(a1), "r"(a2), "r"(a3), "r"(b0), "r"(b1));
}
template <int A> __device__ __forceinline__ void mmap(int lim, float* d, const uint32_t* a, const uint32_t* b) {
    if (A == 0) { mma(d, a[0], a[1], a[2], a[3], b[0], b[1]); return; }
    asm volatile("{.reg .pred p; setp.ge.s32 p, %10, %11;\n"
                 "@p mma.sync.aligned.m16n8k16.row.col.f32.bf16.bf16.f32 {%0,%1,%2,%3},{%4,%5,%6,%7},{%8,%9},{%0,%1,%2,%3};}"
                 : "+f"(d[0]), "+f"(d[1]), "+f"(d[2]), "+f"(d[3]) : "r"(a[0]), "r"(a[1]), "r"(a[2]), "r"(a[3]), "r"(b[0]), "r"(b[1]), "r"(lim), "n"(A));
}
template <int A> __device__ __forceinline__ void mmar(int lim, float* d, const float* c, const uint32_t* a, const uint32_t* b) {
    if (A == 0) {
        asm volatile("mma.sync.aligned.m16n8k16.row.col.f32.bf16.bf16.f32 {%0,%1,%2,%3},{%4,%5,%6,%7},{%8,%9},{%10,%11,%12,%13};"
                     : "=f"(d[0]), "=f"(d[1]), "=f"(d[2]), "=f"(d[3])
                     : "r"(a[0]), "r"(a[1]), "r"(a[2]), "r"(a[3]), "r"(b[0]), "r"(b[1]), "f"(c[0]), "f"(c[1]), "f"(c[2]), "f"(c[3]));
        return;
    }
    asm volatile("{.reg .pred p; setp.ge.s32 p, %14, %15;\n"
                 "@p mma.sync.aligned.m16n8k16.row.col.f32.bf16.bf16.f32 {%0,%1,%2,%3},{%4,%5,%6,%7},{%8,%9},{%10,%11,%12,%13};}"
                 : "+f"(d[0]), "+f"(d[1]), "+f"(d[2]), "+f"(d[3])
                 : "r"(a[0]), "r"(a[1]), "r"(a[2]), "r"(a[3]), "r"(b[0]), "r"(b[1]), "f"(c[0]), "f"(c[1]), "f"(c[2]), "f"(c[3]), "r"(lim), "n"(A));
}
__device__ __forceinline__ uint32_t cpy(uint32_t a, uint32_t z, int k) { return a + z * (uint32_t)k; }

#define WG_FENCE() asm volatile("wgmma.fence.sync.aligned;" ::: "memory")
#define WG_COMMIT() asm volatile("wgmma.commit_group.sync.aligned;" ::: "memory")
#define WG_WAIT(n) asm volatile("wgmma.wait_group.sync.aligned " #n ";" ::: "memory")
template <int N> __device__ __forceinline__ void pin(float* d) {
#pragma unroll
    for (int i = 0; i < N; i++) asm volatile("" : "+f"(d[i])::"memory");
}
template <int N> __device__ __forceinline__ void pinu(uint32_t* d) {
#pragma unroll
    for (int i = 0; i < N; i++) asm volatile("" : "+r"(d[i])::"memory");
}
__device__ __forceinline__ uint64_t mkdesc(uint32_t addr, uint32_t lbo, uint32_t sbo, uint32_t sw) {
    return (uint64_t)((addr & 0x3FFFF) >> 4) | ((uint64_t)(lbo >> 4) << 16) | ((uint64_t)(sbo >> 4) << 32) | ((uint64_t)sw << 62);
}
template <int TA> __device__ __forceinline__ void wgmma_ss64(float* d, uint64_t da, uint64_t db, int sd) {
    asm volatile("{.reg .pred p; setp.ne.b32 p, %34, 0;\n"
                 "wgmma.mma_async.sync.aligned.m64n64k16.f32.bf16.bf16 {%0, %1, %2, %3, %4, %5, %6, %7, %8, %9, %10, %11, %12, %13, %14, %15, %16, %17, %18, %19, %20, %21, %22, %23, %24, %25, %26, %27, %28, %29, %30, %31}, %32, %33, p, 1, 1, %35, 1;}"
                 : "+f"(d[0]), "+f"(d[1]), "+f"(d[2]), "+f"(d[3]), "+f"(d[4]), "+f"(d[5]), "+f"(d[6]), "+f"(d[7]),
                   "+f"(d[8]), "+f"(d[9]), "+f"(d[10]), "+f"(d[11]), "+f"(d[12]), "+f"(d[13]), "+f"(d[14]), "+f"(d[15]),
                   "+f"(d[16]), "+f"(d[17]), "+f"(d[18]), "+f"(d[19]), "+f"(d[20]), "+f"(d[21]), "+f"(d[22]), "+f"(d[23]),
                   "+f"(d[24]), "+f"(d[25]), "+f"(d[26]), "+f"(d[27]), "+f"(d[28]), "+f"(d[29]), "+f"(d[30]), "+f"(d[31])
                 : "l"(da), "l"(db), "r"(sd), "n"(TA));
}
__device__ __forceinline__ void wgmma_ss224(float* d, uint64_t da, uint64_t db, int sd) {
    asm volatile("{.reg .pred p; setp.ne.b32 p, %114, 0;\n"
                 "wgmma.mma_async.sync.aligned.m64n224k16.f32.bf16.bf16 {%0, %1, %2, %3, %4, %5, %6, %7, %8, %9, %10, %11, %12, %13, %14, %15, %16, %17, %18, %19, %20, %21, %22, %23, %24, %25, %26, %27, %28, %29, %30, %31, %32, %33, %34, %35, %36, %37, %38, %39, %40, %41, %42, %43, %44, %45, %46, %47, %48, %49, %50, %51, %52, %53, %54, %55, %56, %57, %58, %59, %60, %61, %62, %63, %64, %65, %66, %67, %68, %69, %70, %71, %72, %73, %74, %75, %76, %77, %78, %79, %80, %81, %82, %83, %84, %85, %86, %87, %88, %89, %90, %91, %92, %93, %94, %95, %96, %97, %98, %99, %100, %101, %102, %103, %104, %105, %106, %107, %108, %109, %110, %111}, %112, %113, p, 1, 1, %115, 1;}"
                 : "+f"(d[0]), "+f"(d[1]), "+f"(d[2]), "+f"(d[3]), "+f"(d[4]), "+f"(d[5]), "+f"(d[6]), "+f"(d[7]),
                   "+f"(d[8]), "+f"(d[9]), "+f"(d[10]), "+f"(d[11]), "+f"(d[12]), "+f"(d[13]), "+f"(d[14]), "+f"(d[15]),
                   "+f"(d[16]), "+f"(d[17]), "+f"(d[18]), "+f"(d[19]), "+f"(d[20]), "+f"(d[21]), "+f"(d[22]), "+f"(d[23]),
                   "+f"(d[24]), "+f"(d[25]), "+f"(d[26]), "+f"(d[27]), "+f"(d[28]), "+f"(d[29]), "+f"(d[30]), "+f"(d[31]),
                   "+f"(d[32]), "+f"(d[33]), "+f"(d[34]), "+f"(d[35]), "+f"(d[36]), "+f"(d[37]), "+f"(d[38]), "+f"(d[39]),
                   "+f"(d[40]), "+f"(d[41]), "+f"(d[42]), "+f"(d[43]), "+f"(d[44]), "+f"(d[45]), "+f"(d[46]), "+f"(d[47]),
                   "+f"(d[48]), "+f"(d[49]), "+f"(d[50]), "+f"(d[51]), "+f"(d[52]), "+f"(d[53]), "+f"(d[54]), "+f"(d[55]),
                   "+f"(d[56]), "+f"(d[57]), "+f"(d[58]), "+f"(d[59]), "+f"(d[60]), "+f"(d[61]), "+f"(d[62]), "+f"(d[63]),
                   "+f"(d[64]), "+f"(d[65]), "+f"(d[66]), "+f"(d[67]), "+f"(d[68]), "+f"(d[69]), "+f"(d[70]), "+f"(d[71]),
                   "+f"(d[72]), "+f"(d[73]), "+f"(d[74]), "+f"(d[75]), "+f"(d[76]), "+f"(d[77]), "+f"(d[78]), "+f"(d[79]),
                   "+f"(d[80]), "+f"(d[81]), "+f"(d[82]), "+f"(d[83]), "+f"(d[84]), "+f"(d[85]), "+f"(d[86]), "+f"(d[87]),
                   "+f"(d[88]), "+f"(d[89]), "+f"(d[90]), "+f"(d[91]), "+f"(d[92]), "+f"(d[93]), "+f"(d[94]), "+f"(d[95]),
                   "+f"(d[96]), "+f"(d[97]), "+f"(d[98]), "+f"(d[99]), "+f"(d[100]), "+f"(d[101]), "+f"(d[102]), "+f"(d[103]),
                   "+f"(d[104]), "+f"(d[105]), "+f"(d[106]), "+f"(d[107]), "+f"(d[108]), "+f"(d[109]), "+f"(d[110]), "+f"(d[111])
                 : "l"(da), "l"(db), "r"(sd), "n"(0));
}
__device__ __forceinline__ void wgmma_rs64(float* d, uint32_t a0, uint32_t a1, uint32_t a2, uint32_t a3, uint64_t db, int sd) {
    asm volatile("{.reg .pred p; setp.ne.b32 p, %37, 0;\n"
                 "wgmma.mma_async.sync.aligned.m64n64k16.f32.bf16.bf16 {%0, %1, %2, %3, %4, %5, %6, %7, %8, %9, %10, %11, %12, %13, %14, %15, %16, %17, %18, %19, %20, %21, %22, %23, %24, %25, %26, %27, %28, %29, %30, %31}, {%32, %33, %34, %35}, %36, p, 1, 1, 1;}"
                 : "+f"(d[0]), "+f"(d[1]), "+f"(d[2]), "+f"(d[3]), "+f"(d[4]), "+f"(d[5]), "+f"(d[6]), "+f"(d[7]),
                   "+f"(d[8]), "+f"(d[9]), "+f"(d[10]), "+f"(d[11]), "+f"(d[12]), "+f"(d[13]), "+f"(d[14]), "+f"(d[15]),
                   "+f"(d[16]), "+f"(d[17]), "+f"(d[18]), "+f"(d[19]), "+f"(d[20]), "+f"(d[21]), "+f"(d[22]), "+f"(d[23]),
                   "+f"(d[24]), "+f"(d[25]), "+f"(d[26]), "+f"(d[27]), "+f"(d[28]), "+f"(d[29]), "+f"(d[30]), "+f"(d[31])
                 : "r"(a0), "r"(a1), "r"(a2), "r"(a3), "l"(db), "r"(sd));
}


template <int NV> __device__ __forceinline__ float aux_reduce(float* v, uint32_t red, int at) {
    const int lane = at & 31, aw = at >> 5;
    int idx;
    if (NV == 16) {
        halve<16>(v, 16, lane & 16); halve<8>(v, 8, lane & 8); halve<4>(v, 4, lane & 4); halve<2>(v, 2, lane & 2);
        v[0] += shx(v[0], 1); idx = lane >> 1;
    } else {
        halve<8>(v, 16, lane & 16); halve<4>(v, 8, lane & 8); halve<2>(v, 4, lane & 4);
        v[0] += shx(v[0], 2); v[0] += shx(v[0], 1); idx = lane >> 2;
    }
    stsf(red + (aw * 16 + idx) * 4, v[0]);
    bar_sync(4, 128);
    const uint32_t a = red + (at & 15) * 4;
    return (ldsf(a) + ldsf(a + 64)) + (ldsf(a + 128) + ldsf(a + 192));
}

__device__ __forceinline__ uint32_t wstage(int q) { return (q & 1) * 28672 + (q & 2) * 32768; }

__global__ void __launch_bounds__(384, 1)
fused_kernel(const Params P, const __grid_constant__ CUtensorMap tmX2, const __grid_constant__ CUtensorMap tmG,
             const __grid_constant__ CUtensorMap tmX1, const __grid_constant__ CUtensorMap tmW1,
             const __grid_constant__ CUtensorMap tmW2, const __grid_constant__ CUtensorMap tmW3,
             const __grid_constant__ CUtensorMap tmW4)
{
    extern __shared__ __align__(1024) uint8_t smem_raw[];
    const uint32_t sb = __shfl_sync(0xffffffffu, (uint32_t)__cvta_generic_to_shared(smem_raw), 0);
    const int tid = threadIdx.x, lane = tid & 31, warp = __shfl_sync(0xffffffffu, tid >> 5, 0), g = lane >> 2, q = lane & 3;
    const int cl = blockIdx.x >> 1, pr = blockIdx.x & 1;
    int gi, pa;
    if (cl < 4) { gi = 15; pa = cl; } else if (cl < 36) { gi = (cl - 4) & 7; pa = (cl - 4) >> 3; } else { gi = 8 + (cl - 36) % 7; pa = (cl - 36) / 7; }
    const int fs = 2 * pa + pr;
    const int cs = 4 * pr + pa;
    const int b = 8 * gi + fs;
    const uint32_t bar0 = sb + SM_BAR;
#define BAR(i) (bar0 + 8 * (i))

    if (warp < 8) {
        const int s = warp >> 2, w4 = warp & 3, wt = tid & 127;
        const size_t po = (size_t)b * 512 + 2 * tid;
        const uint32_t pAre = ldg32(P.Are + po), pAim = ldg32(P.Aim + po), pBre = ldg32(P.Bre + po), pBim = ldg32(P.Bim + po),
                       pCre = ldg32(P.Cre + po), pCim = ldg32(P.Cim + po);
        const float ldt = __bfloat162float(P.logdt[4 * b + (tid >> 6)]);
        const float dsk = __bfloat162float(P.dskip[4 * b + w4]);
        const uint32_t ep = ldr32(&g_epoch[b]) + 1;
        const int ua = tid >> 3, rho = tid & 7;
        uint2 xc[2][5];
#pragma unroll
        for (int u = 0; u < 2; u++)
#pragma unroll
            for (int i = 0; i < 5; i++) {
                const int t = min(32 * (ua + 32 * u) + rho + 8 * i, 2047);
                xc[u][i] = ldg64(P.x + (size_t)t * 512 + 4 * b);
            }
        for (int i = tid; i < 4 * WD_B / 16; i += 256) sts128(sb + SM_WD + i * 16, make_uint4(0, 0, 0, 0));
        if (tid < 152) sts128(sb + SM_UW + (tid / 38) * UW_B + (tid % 38) * 16, make_uint4(0, 0, 0, 0));
        {
            const int ch = tid >> 6;
            const uint32_t qp = sb + (ch < 2 ? ch * QP_B : SM_Q + 16384 + (ch - 2) * QP_B) + (tid & 63) * 8;
            const float dt = bround(expf(ldt));
            cf z[2], z8[2], w[2], Q[2];
#pragma unroll
            for (int m = 0; m < 2; m++) {
                const float a = dt * (m ? bhi(pAre) : blo(pAre)) * 1.4426950408889634f, th = dt * (m ? bhi(pAim) : blo(pAim));
                z[m] = cexp2(a, -th); z8[m] = cexp2(8.f * a, 8.f * th); w[m] = cexp2(256.f * a, -256.f * th);
                cf C, B;
                C.x = m ? bhi(pCre) : blo(pCre); C.y = m ? bhi(pCim) : blo(pCim);
                B.x = dt * (m ? bhi(pBre) : blo(pBre)); B.y = dt * (m ? bhi(pBim) : blo(pBim));
                Q[m] = cmul(C, B);
            }
#pragma unroll 4
            for (int i = 0; i < 32; i++) {
                sts64(qp + i * QP_PITCH, pack2(Q[0].x, Q[0].y), pack2(Q[1].x, Q[1].y));
                Q[0] = cmul(Q[0], z8[0]); Q[1] = cmul(Q[1], z8[1]);
            }
            const uint32_t pp = qp + 32 * QP_PITCH;
#define PST(j, v) sts64(pp + (j) * QP_PITCH, pack2(v[0].x, v[0].y), pack2(v[1].x, v[1].y))
#define CM(d, a, c) d[0] = cmul(a[0], c[0]); d[1] = cmul(a[1], c[1])
            cf z2[2], z3[2], z4[2], z6[2], t[2], w2[2], w3[2], w4_[2];
            sts64(pp, 0x3F80u, 0x3F80u);
            PST(1, z); CM(z2, z, z); PST(2, z2); CM(z3, z2, z); PST(3, z3); CM(z4, z2, z2); PST(4, z4);
            CM(t, z4, z); PST(5, t); CM(z6, z4, z2); PST(6, z6); CM(t, z4, z3); PST(7, t);
            PST(8, w); CM(t, w, z2); PST(9, t); CM(t, w, z4); PST(10, t); CM(t, w, z6); PST(11, t);
            CM(w2, w, w); PST(12, w2); CM(t, w2, z4); PST(13, t); CM(w3, w2, w); PST(14, w3); CM(t, w3, z4); PST(15, t);
            CM(w4_, w2, w2); PST(16, w4_); CM(t, w4_, w); PST(17, t); CM(t, w4_, w2); PST(18, t); CM(t, w4_, w3); PST(19, t);
            CM(t, w4_, w4_); PST(20, t);
#undef PST
#undef CM
        }
        bar_sync(5, 384);
        uint2 st[2][5];
#pragma unroll
        for (int u = 0; u < 2; u++)
#pragma unroll
            for (int i = 0; i < 5; i++) st[u][i] = ldr64(&g_stats0[min(32 * (ua + 32 * u) + rho + 8 * i, 2047)]);
        {
            const uint32_t qp = sb + (w4 < 2 ? w4 * QP_B : SM_Q + 16384 + (w4 - 2) * QP_B);
            const uint32_t aa = qp + (16 * s + (lane & 15)) * QP_PITCH + (lane >> 4) * 16;
            const uint32_t ba = qp + (32 + (lane & 7)) * QP_PITCH + (lane >> 3) * 16;
            float G[3][4];
#pragma unroll
            for (int n = 0; n < 3; n++) G[n][0] = G[n][1] = G[n][2] = G[n][3] = 0.f;
#pragma unroll 2
            for (int k = 0; k < 8; k++) {
                uint32_t a0[4], a1[4], bb[3][4];
                ldsm4(a0, aa + k * 64); ldsm4(a1, aa + k * 64 + 32);
#pragma unroll
                for (int n = 0; n < 3; n++) ldsm4(bb[n], ba + n * 8 * QP_PITCH + k * 64);
#pragma unroll
                for (int n = 0; n < 3; n++) mma(G[n], a0[0], a0[1], a0[2], a0[3], bb[n][0], bb[n][1]);
#pragma unroll
                for (int n = 0; n < 3; n++) mma(G[n], a1[0], a1[1], a1[2], a1[3], bb[n][2], bb[n][3]);
            }
            if (s == 0 && lane == 0) G[0][0] += dsk;
            constexpr uint64_t CB[3][2] = {
                {(uint64_t)T0o | ((uint64_t)T2o << 16) | ((uint64_t)T4o << 32) | ((uint64_t)(TM2o + 1) << 48),
                 (uint64_t)T1o | ((uint64_t)T3o << 16) | ((uint64_t)T5o << 32) | ((uint64_t)(TM1o + 1) << 48)},
                {(uint64_t)(T0o + 32) | ((uint64_t)(T4o + 32) << 16) | ((uint64_t)(T0o + 64) << 32) | ((uint64_t)(T0o + 96) << 48),
                 (uint64_t)(T2o + 32) | ((uint64_t)(TM2o + 33) << 16) | ((uint64_t)(T4o + 64) << 32) | ((uint64_t)(T4o + 96) << 48)},
                {(uint64_t)(T0o + 128) | ((uint64_t)(T0o + 192) << 16) | ((uint64_t)(T0o + 256) << 32),
                 (uint64_t)(T0o + 160) | ((uint64_t)(T0o + 224) << 16)}};
            const uint32_t wd = sb + SM_WD + w4 * WD_B + (16 * s + g) * 4;
#pragma unroll
            for (int n = 0; n < 3; n++)
#pragma unroll
                for (int e = 0; e < 2; e++) {
                    const uint32_t a = wd + 4 * (uint32_t)((CB[n][e] >> (16 * q)) & 0xFFFF);
                    const uint32_t v = pack2(G[n][e], G[n][2 + e]);
                    const bool ok0 = n < 2 || q < 2 || (e == 0 && q == 2 && s == 0), ok1 = n < 2 || q < 2;
                    if (ok0) { sts16(a, v); sts16(a + 6, v); }
                    if (ok1) { sts16(a + 32, v >> 16); sts16(a + 38, v >> 16); }
                }
        }
        {
            int it = 0;
            for (;;) {
                bool ok = true;
#pragma unroll
                for (int u = 0; u < 2; u++)
#pragma unroll
                    for (int i = 0; i < 5; i++) ok = ok && st[u][i].x != 0 && st[u][i].y != 0;
                if (ok) break;
                if (++it > SPIN_MAX) __trap();
#pragma unroll
                for (int u = 0; u < 2; u++)
#pragma unroll
                    for (int i = 0; i < 5; i++)
                        if (st[u][i].x == 0 || st[u][i].y == 0) st[u][i] = ldr64(&g_stats0[min(32 * (ua + 32 * u) + rho + 8 * i, 2047)]);
            }
            mbar_wait(BAR(B_MOD));
            const uint4 sa4 = lds128(sb + SM_OWN), ca4 = lds128(sb + SM_OWN + 16);
            const float sa[4] = {__uint_as_float(sa4.x), __uint_as_float(sa4.y), __uint_as_float(sa4.z), __uint_as_float(sa4.w)};
            const float ca[4] = {__uint_as_float(ca4.x), __uint_as_float(ca4.y), __uint_as_float(ca4.z), __uint_as_float(ca4.w)};
#pragma unroll
            for (int u = 0; u < 2; u++) {
                const int a = ua + 32 * u;
                float h[5][4];
#pragma unroll
                for (int i = 0; i < 5; i++) {
                    const float m = __uint_as_float(~st[u][i].x), r = __uint_as_float(~st[u][i].y);
                    h[i][0] = fmaf((blo(xc[u][i].x) - m) * r, ca[0], sa[0]);
                    h[i][1] = fmaf((bhi(xc[u][i].x) - m) * r, ca[1], sa[1]);
                    h[i][2] = fmaf((blo(xc[u][i].y) - m) * r, ca[2], sa[2]);
                    h[i][3] = fmaf((bhi(xc[u][i].y) - m) * r, ca[3], sa[3]);
                }
                if (u == 1 && a == 63) h[4][0] = h[4][1] = h[4][2] = h[4][3] = 0.f;
                const uint32_t ub = sb + SM_UW + 4 * (40 * (a + 4) + rho + 5), pad = rho >= 3 ? 32 : 0;
                const uint32_t xb = sb + SM_XS + 4 * (40 * a + rho);
#pragma unroll
                for (int i = 0; i < 4; i++) {
#pragma unroll
                    for (int c = 0; c < 4; c++) sts32(ub + c * UW_B + 32 * i + (i == 3 ? pad : 0), pack2(h[i][c], h[i + 1][c]));
                    sts32(xb + 32 * i, xc[u][i].x); sts32(xb + XS_B + 32 * i, xc[u][i].y);
                }
                if (u == 0 && a == 0) {
#pragma unroll
                    for (int c = 0; c < 4; c++) sts32(sb + SM_UW + c * UW_B + 4 * (rho + 149) + pad, pack2(0.f, h[0][c]));
                }
            }
        }
        fence_async_smem();
        bar_sync(1, 256);
        if (tid == 0) {
            mbar_expect(BAR(B_W1FULL), 65536);
            tma2d(sb + SM_W1, &tmW1, 64 * cs, 0, BAR(B_W1FULL));
            tma2d(sb + SM_W1 + 32768, &tmW1, 64 * cs, 256, BAR(B_W1FULL));
        }
        asm volatile("setmaxnreg.inc.sync.aligned.u32 216;");
        {
            const int o = g - 2 * q;
            const uint32_t wd = sb + SM_WD + w4 * WD_B + 4 * o;
            const uint32_t sel0 = (o >= 0 ? 0x54u : 0x10u) | (o >= 1 ? 0x7600u : 0x3200u);
            uint32_t ub = sb + SM_UW + w4 * UW_B + 4 * (16 * q + 8 * (q >> 1) + g);
            uint32_t fa = sb + SM_FAR + w4 * 6144 + lane * 16;
            const float zero4[4] = {0.f, 0.f, 0.f, 0.f};
            const uint32_t oz = lds32(sb + SM_UW);
            uint32_t f[9][2];
#define LT(T, h) lds32(wd + 4 * ((T) + 8 * (h)))
#define LF(k) { f[k][0] = lds32(ub + (8 - (k)) * 4); f[k][1] = lds32(ub + 320 + (8 - (k)) * 4); }
#define QUAD(Q, a0, a1, a2, a3, id) { Q[0] = a0; Q[1] = a1; Q[2] = cpy(a2, oz, 2 * (id) + 3); Q[3] = cpy(a3, oz, 2 * (id) + 4); }
#define QF(Q, X, L, id) QUAD(Q, X[2 * (L)], X[2 * (L) + 1], (L) ? X[(L) ? 2 * (L) - 1 : 0] : 0u, X[2 * (L)], id)
#define SUM3(d, a, c, e) { d[0] = hadd2(hadd2(f[a][0], f[c][0]), f[e][0]); d[1] = hadd2(hadd2(f[a][1], f[c][1]), f[e][1]); }
#define SUMX(d, p, a, c) { d[0] = hadd2(p[0], hadd2(f[a][0], f[c][0])); d[1] = hadd2(p[1], hadd2(f[a][1], f[c][1])); }
            if (s) {
                uint32_t A[8][3][4], A3[4][2][4];
                {
                    const uint32_t sel1 = (o >= 1 ? 0x54u : 0x10u) | (o >= 2 ? 0x7600u : 0x3200u);
                    uint32_t T0[10], T4[10], X[10];
#pragma unroll
                    for (int h = 0; h < 10; h++) { T0[h] = LT(T0o, h); T4[h] = LT(T4o, h); }
#pragma unroll
                    for (int L = 0; L < 3; L++) { QF(A[2][L], T0, L, 0) QF(A[6][L], T4, L, 1) }
#pragma unroll
                    for (int L = 3; L < 5; L++) { QF(A3[1][L - 3], T0, L, 0) QF(A3[3][L - 3], T4, L, 1) }
#pragma unroll
                    for (int k = 0; k < 2; k++) {
#pragma unroll
                        for (int h = 0; h < 9; h++) X[h] = LT(k ? T2o : TM2o, h);
                        X[8] = prmt(X[8], T0[8], k ? sel0 : sel1); X[9] = cpy(T0[9], oz, 31 + k);
#pragma unroll
                        for (int L = 0; L < 3; L++) QF(A[4 * k][L], X, L, 2 + k)
#pragma unroll
                        for (int L = 3; L < 5; L++) QF(A3[2 * k][L - 3], X, L, 2 + k)
                    }
#pragma unroll
                    for (int k = 0; k < 4; k++) {
#pragma unroll
                        for (int h = 0; h < 5; h++) X[h] = LT(k == 0 ? TM1o : k == 1 ? T1o : k == 2 ? T3o : T5o, h);
                        X[4] = prmt(X[4], k < 2 ? T0[4] : T4[4], k ? sel0 : sel1); X[5] = cpy(k < 2 ? T0[5] : T4[5], oz, 33 + k);
#pragma unroll
                        for (int L = 0; L < 3; L++) QF(A[2 * k + 1][L], X, L, 4 + k)
                    }
                }
                float Pa[5][4], Ra[3][4];
                uint32_t u3[2];
                LF(1) LF(2)
                mmar<0>(0, Pa[1], zero4, A[0][1], f[1]); mmar<0>(0, Pa[2], zero4, A[0][2], f[1]);
                mmar<0>(0, Pa[3], zero4, A3[0][0], f[1]); mmar<0>(0, Pa[4], zero4, A3[0][1], f[1]);
                mmar<0>(0, Ra[1], zero4, A[1][1], f[2]); mmar<0>(0, Ra[2], zero4, A[1][2], f[2]);
                mmap<0>(0, Pa[3], A3[1][0], f[2]); mmap<0>(0, Pa[4], A3[1][1], f[2]);
                ub += 640;
                LF(1) LF(2) LF(3) LF(4) LF(5) LF(6) LF(7) LF(8)
                uint32_t xa = sb + SM_XS + (w4 >> 1) * XS_B + 4 * (8 * g + 2 * q + 8 * (g >> 2));
                bf16* xo = g_x2t + (size_t)(4 * b + w4) * 2048 + 8 * g + 2 * q;
                const uint32_t xsel = (w4 & 1) ? 0x3244u : 0x1044u;
                float ga = 0.f;
#pragma unroll 1
                for (int lim = 15; lim >= 0; lim--) {
                    ub += lim ? 640 : 0;
                    SUM3(u3, 2, 4, 3)
                    mmar<0>(lim, Pa[0], Pa[1], A[0][0], f[1]); mmar<1>(lim, Pa[1], Pa[2], A[0][1], f[1]); mmar<2>(lim, Pa[2], Pa[3], A[0][2], f[1]);
                    mmar<3>(lim, Pa[3], Pa[4], A3[0][0], f[1]); mmar<4>(lim, Pa[4], zero4, A3[0][1], f[1]); LF(1)
                    mmar<0>(lim, Ra[0], Ra[1], A[1][0], f[2]); mmar<1>(lim, Ra[1], Ra[2], A[1][1], f[2]); mmar<2>(lim, Ra[2], zero4, A[1][2], f[2]); LF(2)
                    mmap<0>(lim, Pa[0], A[2][0], f[3]); mmap<1>(lim, Pa[1], A[2][1], f[3]); mmap<2>(lim, Pa[2], A[2][2], f[3]); LF(3)
                    mmap<3>(lim, Pa[3], A3[1][0], u3); mmap<4>(lim, Pa[4], A3[1][1], u3);
                    SUM3(u3, 6, 8, 7)
                    mmap<0>(lim, Ra[0], A[3][0], f[4]); mmap<1>(lim, Ra[1], A[3][1], f[4]); mmap<2>(lim, Ra[2], A[3][2], f[4]); LF(4)
                    mmap<0>(lim, Pa[0], A[4][0], f[5]); mmap<1>(lim, Pa[1], A[4][1], f[5]); mmap<2>(lim, Pa[2], A[4][2], f[5]);
                    mmap<3>(lim, Pa[3], A3[2][0], f[5]); mmap<4>(lim, Pa[4], A3[2][1], f[5]); LF(5)
                    mmap<0>(lim, Ra[0], A[5][0], f[6]); mmap<1>(lim, Ra[1], A[5][1], f[6]); mmap<2>(lim, Ra[2], A[5][2], f[6]); LF(6)
                    mmap<0>(lim, Pa[0], A[6][0], f[7]); mmap<0>(lim, Ra[0], A[7][0], f[8]);
                    const uint2 x0 = lds64(xa), x1 = lds64(xa + 320);
                    mmap<1>(lim, Pa[1], A[6][1], f[7]); mmap<2>(lim, Pa[2], A[6][2], f[7]); LF(7)
                    mmap<1>(lim, Ra[1], A[7][1], f[8]); mmap<2>(lim, Ra[2], A[7][2], f[8]); LF(8)
                    mmap<3>(lim, Pa[3], A3[3][0], u3); mmap<4>(lim, Pa[4], A3[3][1], u3);
                    uint4 fv = make_uint4(0, 0, 0, 0);
                    if (lim == 15) { mbar_wait(BAR(B_MOD + 1)); ga = ldsf(sb + SM_OWN + 32 + 4 * w4); }
                    if (lim <= 11) { mbar_wait(BAR(B_FAR + 11 - lim)); fv = lds128(fa); fa += 512; }
                    stg32(xo, pack2(fmaf(ga, Pa[0][0] + Ra[0][0] + __uint_as_float(fv.x), __uint_as_float(prmt(x0.x, 0, xsel))),
                                    fmaf(ga, Pa[0][1] + Ra[0][1] + __uint_as_float(fv.y), __uint_as_float(prmt(x0.y, 0, xsel)))));
                    stg32(xo + 64, pack2(fmaf(ga, Pa[0][2] + Ra[0][2] + __uint_as_float(fv.z), __uint_as_float(prmt(x1.x, 0, xsel))),
                                         fmaf(ga, Pa[0][3] + Ra[0][3] + __uint_as_float(fv.w), __uint_as_float(prmt(x1.y, 0, xsel)))));
                    xa += 640; xo += 128;
                    if (lim == 7) { warp_arrive(BAR(B_CONV)); }
                }
                warp_arrive(BAR(B_CONV + 1));
            } else {
                uint32_t A0[11][4], A4[11][4], A83[4], A85[4], A16[4];
                {
                    const uint32_t selp = (g & 1) ? 0x7610u : 0x1010u;
                    uint32_t T0[33], T4[32];
#pragma unroll
                    for (int h = 9; h < 33; h++) T0[h] = LT(T0o, h);
#pragma unroll
                    for (int h = 9; h < 17; h++) T4[h] = LT(T4o, h);
                    const uint32_t T3x = prmt(T4[16], T0[16], sel0), T5x = prmt(T4[16], LT(T0o + 1, 16), sel0), T5y = LT(T0o + 1, 17);
                    QUAD(A83, T3x, cpy(T0[17], oz, 31), T4[15], T3x, 2)
                    QUAD(A85, q ? T5x : (T5x & 0xFFFF0000u), q ? T5y : (T5y & 0xFFFF0000u), T4[15], T5x, 3)
#pragma unroll
                    for (int h = 16; h < 32; h++) {
                        const uint32_t v = prmt(lds32(wd + 4 * (g & 1) + 4 * (T0o + 8 * h)), T0[h], selp);
                        T4[h] = h == 16 ? prmt(T4[16], v, sel0) : v;
                    }
                    QUAD(A16, 0u, 0u, T0[31], q == 3 ? (T0[32] & 0xFFFF0000u) : 0u, 4)
#pragma unroll
                    for (int L = 5; L < 16; L++) { QF(A0[L - 5], T0, L, 0) QF(A4[L - 5], T4, L, 1) }
                }
                float Fa[12][4];
                uint32_t u3[2], u5[2], u7[2], f7[2];
                LF(0) LF(1) LF(2)
                u5[0] = hadd2(f[1][0], f[2][0]); u5[1] = hadd2(f[1][1], f[2][1]); u7[0] = hadd2(u5[0], f[0][0]); u7[1] = hadd2(u5[1], f[0][1]);
#pragma unroll
                for (int a = 0; a < 11; a++) mmar<0>(0, Fa[a], zero4, A0[a], a < 4 ? u5 : u7);
                mmar<0>(0, Fa[11], zero4, A16, u7);
                ub += 640;
                LF(0) LF(1) LF(2) LF(3) LF(4) LF(5) LF(6) LF(7) LF(8)
                sts128(fa, make_uint4(__float_as_uint(Fa[0][0]), __float_as_uint(Fa[0][1]), __float_as_uint(Fa[0][2]), __float_as_uint(Fa[0][3])));
                warp_arrive(BAR(B_FAR));
#pragma unroll 1
                for (int lim = 10; lim >= 0; lim--) {
                    ub += 640; fa += 512;
                    SUM3(u5, 2, 4, 3) SUM3(u3, 6, 8, 7) SUMX(u5, u5, 1, 5) SUMX(u7, u5, 0, 6)
                    f7[0] = f[7][0]; f7[1] = f[7][1];
                    LF(0) LF(1) LF(2) LF(3) LF(4) LF(5) LF(7)
                    mmar<0>(lim, Fa[0], Fa[1], A4[0], u3); mmar<1>(lim, Fa[1], Fa[2], A4[1], u3); mmar<2>(lim, Fa[2], Fa[3], A4[2], u3);
                    mmar<3>(lim, Fa[3], Fa[4], A83, f[6]); LF(6)
                    mmar<4>(lim, Fa[4], Fa[5], A4[4], f7); mmap<0>(lim, Fa[0], A0[0], u5);
                    mmar<5>(lim, Fa[5], Fa[6], A4[5], f7); mmar<6>(lim, Fa[6], Fa[7], A4[6], f7);
                    mmap<3>(lim, Fa[3], A85, f[8]); LF(8)
                    mmar<7>(lim, Fa[7], Fa[8], A4[7], f7); mmar<8>(lim, Fa[8], Fa[9], A4[8], f7);
                    mmar<9>(lim, Fa[9], Fa[10], A4[9], f7); mmar<10>(lim, Fa[10], Fa[11], A4[10], f7);
                    mmap<3>(lim, Fa[3], A4[3], f7);
                    sts128(fa, make_uint4(__float_as_uint(Fa[0][0]), __float_as_uint(Fa[0][1]), __float_as_uint(Fa[0][2]), __float_as_uint(Fa[0][3])));
                    mmap<1>(lim, Fa[1], A0[1], u5); mmap<2>(lim, Fa[2], A0[2], u5); mmap<4>(lim, Fa[4], A0[4], u7); mmap<5>(lim, Fa[5], A0[5], u7);
                    mmap<3>(lim, Fa[3], A0[3], u5);
                    mmap<6>(lim, Fa[6], A0[6], u7); mmap<7>(lim, Fa[7], A0[7], u7); mmap<8>(lim, Fa[8], A0[8], u7);
                    mmap<9>(lim, Fa[9], A0[9], u7); mmap<10>(lim, Fa[10], A0[10], u7);
                    warp_arrive(BAR(B_FAR + 11 - lim));
                }
            }
#undef LT
#undef LF
#undef QUAD
#undef QF
#undef SUM3
#undef SUMX
        }

        const int tau = 16 * s + gi, row0 = 64 * tau + 16 * w4 + g;
        float acc[32];
        uint32_t x2p[16];
        {
            float mo[24];
#pragma unroll
            for (int i = 0; i < 24; i++) mo[i] = 0.f;
            const int srow = wt >> 1;
            const uint32_t soff = srow * 128 + ((cs ^ (srow & 7)) << 4) + (wt & 1) * 8;
            const uint32_t xoff = (8 * (lane >> 4) + (lane & 7)) * 128 + (((2 * w4 + ((lane >> 3) & 1)) ^ (lane & 7)) << 4);
            mbar_wait(BAR(B_W1SC));
            int slot = (8 * s) % NSLOT;
#pragma unroll 1
            for (int c = 0; c < 8; c++) {
                const uint32_t ta = sb + SM_Q + slot * 8192;
                mbar_wait(BAR(B_FULL + 8 * s + c));
                const uint64_t da = mkdesc(ta, 8192, 1024, 1), db = mkdesc(sb + SM_W1 + c * 8192, 8192, 1024, 1);
                WG_FENCE();
#pragma unroll
                for (int k = 0; k < 4; k++) wgmma_ss64<1>(acc, da + 128 * k, db + 128 * k, (c | k) != 0);
                WG_COMMIT();
                const uint2 xv = lds64(ta + soff);
                const float2 cv = ldsf2(sb + SM_CS + (64 * c + srow) * 8);
                const float xx[4] = {blo(xv.x), bhi(xv.x), blo(xv.y), bhi(xv.y)};
#pragma unroll
                for (int t = 0; t < 4; t++) {
                    const float y = xx[t] * cv.x;
                    mo[6 * t] += xx[t]; mo[6 * t + 1] = fmaf(xx[t], xx[t], mo[6 * t + 1]); mo[6 * t + 2] += y;
                    mo[6 * t + 3] = fmaf(y, y, mo[6 * t + 3]); mo[6 * t + 4] = fmaf(y, cv.x, mo[6 * t + 4]); mo[6 * t + 5] = fmaf(y, cv.y, mo[6 * t + 5]);
                }
                if (c == cs) {
#pragma unroll
                    for (int n = 0; n < 4; n++) ldsm4t(x2p + 4 * n, ta + xoff + n * 2048);
                }
                if (c) { WG_WAIT(1); warp_arrive(BAR(B_EMPTY + 8 * s + c - 1)); }
                slot = slot == NSLOT - 1 ? 0 : slot + 1;
            }
            halve<24>(mo, 16, lane & 16); halve<12>(mo, 8, lane & 8); halve<6>(mo, 4, lane & 4);
            mo[0] += shx(mo[0], 2); mo[1] += shx(mo[1], 2); mo[2] += shx(mo[2], 2);
            const uint32_t red = sb + SM_RED + s * 768;
            if (!(lane & 2)) {
                const uint32_t a = red + w4 * 192 + 4 * (24 * (lane & 1) + 6 * (lane >> 3) + 3 * ((lane >> 2) & 1));
                stsf(a, mo[0]); stsf(a + 4, mo[1]); stsf(a + 8, mo[2]);
            }
            bar_sync(2 + s, 128);
            if (wt < 8) {
                float S[6];
#pragma unroll
                for (int k = 0; k < 3; k++) {
                    const uint32_t a = red + 24 * wt + 8 * k;
                    const float2 v0 = ldsf2(a), v1 = ldsf2(a + 192), v2 = ldsf2(a + 384), v3 = ldsf2(a + 576);
                    S[2 * k] = (v0.x + v1.x) + (v2.x + v3.x); S[2 * k + 1] = (v0.y + v1.y) + (v2.y + v3.y);
                }
                const uint4 k4 = lds128(sb + SM_CONST);
                const float Cc = __uint_as_float(k4.x), Cs = __uint_as_float(k4.y), Ccc = __uint_as_float(k4.z), Ccs = __uint_as_float(k4.w), Css = ldsf(sb + SM_CONST + 16);
                const float n1 = 1.f / 512.f;
                const float m1 = S[0] * n1, r1 = rsqrtf(fmaxf(fmaf(-m1, m1, S[1] * n1), 0.f) + LN_EPS);
                const float m2 = fmaf(r1, fmaf(-m1, Cc, S[2]), Cs) * n1;
                const float e2 = (r1 * r1 * (S[3] - 2.f * m1 * S[4] + m1 * m1 * Ccc) + 2.f * r1 * fmaf(-m1, Ccs, S[5]) + Css) * n1;
                const float r2 = rsqrtf(fmaxf(fmaf(-m2, m2, e2), 0.f) + LN_EPS);
                str128(&g_stats1[64 * tau + 8 * cs + wt], make_uint4(__float_as_uint(m1), __float_as_uint(r1), __float_as_uint(m2), __float_as_uint(r2)));
            }
            WG_WAIT(0);
            pin<32>(acc);
            warp_arrive(BAR(B_EMPTY + 8 * s + 7));
            if (lane == 0) mbar_arrive(BAR(B_W1FREE));
            mbar_wait(BAR(B_UREADY));
            uint4 s0, s1; int it = 0;
            do {
                s0 = ldr128(&g_stats1[row0]); s1 = ldr128(&g_stats1[row0 + 8]);
                if (++it > SPIN_MAX) __trap();
            } while (!(valid4(s0) && valid4(s1)));
            const float m1[2] = {__uint_as_float(s0.x), __uint_as_float(s1.x)}, r1[2] = {__uint_as_float(s0.y), __uint_as_float(s1.y)};
            const float r2[2] = {__uint_as_float(s0.w), __uint_as_float(s1.w)};
            const float al[2] = {r2[0] * r1[0], r2[1] * r1[1]}, be[2] = {-al[0] * m1[0], -al[1] * m1[1]};
            const float de[2] = {-r2[0] * __uint_as_float(s0.z), -r2[1] * __uint_as_float(s1.z)};
            uint32_t gp[2][8];
#pragma unroll
            for (int n = 0; n < 8; n++) {
                const uint32_t ua_ = sb + SM_U123 + (8 * n + 2 * q) * 4;
                const float2 u1 = ldsf2(ua_), u2 = ldsf2(ua_ + 256), u3 = ldsf2(ua_ + 512);
#pragma unroll
                for (int r = 0; r < 2; r++) {
                    const float p0 = fmaf(al[r], acc[4 * n + 2 * r], fmaf(be[r], u1.x, fmaf(r2[r], u2.x, de[r] * u3.x)));
                    const float p1 = fmaf(al[r], acc[4 * n + 2 * r + 1], fmaf(be[r], u1.y, fmaf(r2[r], u2.y, de[r] * u3.y)));
                    gp[r][n] = pack2(gelu(p0), gelu(p1));
                }
            }
            bf16* go = g_g + (size_t)row0 * 512 + 64 * cs + 16 * q;
#pragma unroll
            for (int r = 0; r < 2; r++) {
                stg128(go + r * 4096, gp[r][0], gp[r][1], gp[r][2], gp[r][3]);
                stg128(go + r * 4096 + 8, gp[r][4], gp[r][5], gp[r][6], gp[r][7]);
            }
            bar_sync(2 + s, 128);
            if (wt == 0) asm volatile("st.release.gpu.global.b32 [%0], %1;" ::"l"(&g_flag[(tau * 8 + cs) * 32]), "r"(ep) : "memory");
#pragma unroll
            for (int n = 0; n < 8; n++) {
                const uint4 cv = lds128(sb + SM_CS + (64 * cs + 8 * n + 2 * q) * 8);
#pragma unroll
                for (int r = 0; r < 2; r++) {
                    acc[4 * n + 2 * r] = fmaf((blo(x2p[2 * n + r]) - m1[r]) * r1[r], __uint_as_float(cv.x), __uint_as_float(cv.y));
                    acc[4 * n + 2 * r + 1] = fmaf((bhi(x2p[2 * n + r]) - m1[r]) * r1[r], __uint_as_float(cv.z), __uint_as_float(cv.w));
                }
            }
        }
        {
            mbar_wait(BAR(B_W2FULL));
            int slot = (16 + 8 * s) % NSLOT;
#pragma unroll 1
            for (int c = 0; c < 8; c++) {
                mbar_wait(BAR(B_FULL + 16 + 8 * s + c));
                const uint64_t da = mkdesc(sb + SM_Q + slot * 8192, 16, 1024, 1), db = mkdesc(sb + SM_W2 + c * 8192, 8192, 1024, 1);
                WG_FENCE();
#pragma unroll
                for (int k = 0; k < 4; k++) wgmma_ss64<0>(acc, da + 2 * k, db + 128 * k, 1);
                WG_COMMIT();
                if (c) { WG_WAIT(1); warp_arrive(BAR(B_EMPTY + 16 + 8 * s + c - 1)); }
                slot = slot == NSLOT - 1 ? 0 : slot + 1;
            }
            WG_WAIT(0);
            pin<32>(acc);
            warp_arrive(BAR(B_EMPTY + 16 + 8 * s + 7));
            if (lane == 0) mbar_arrive(BAR(B_W2FREE));
            uint32_t xp[2][8];
            float sm[2] = {0.f, 0.f}, sq[2] = {0.f, 0.f};
#pragma unroll
            for (int n = 0; n < 8; n++)
#pragma unroll
                for (int r = 0; r < 2; r++) {
                    xp[r][n] = pack2(acc[4 * n + 2 * r], acc[4 * n + 2 * r + 1]);
                    const float a = blo(xp[r][n]), c = bhi(xp[r][n]);
                    sm[r] += a + c; sq[r] = fmaf(a, a, fmaf(c, c, sq[r]));
                }
            bf16* xo = g_x1 + (size_t)row0 * 512 + 64 * cs + 16 * q;
#pragma unroll
            for (int r = 0; r < 2; r++) {
                stg128(xo + r * 4096, xp[r][0], xp[r][1], xp[r][2], xp[r][3]);
                stg128(xo + r * 4096 + 8, xp[r][4], xp[r][5], xp[r][6], xp[r][7]);
                sm[r] += shx(sm[r], 1); sq[r] += shx(sq[r], 1); sm[r] += shx(sm[r], 2); sq[r] += shx(sq[r], 2);
            }
            if (q < 2) g_stats2[(row0 + 8 * q) * 8 + cs] = q ? make_float2(sm[1], sq[1]) : make_float2(sm[0], sq[0]);
            bar_sync(2 + s, 128);
            if (wt == 0) asm volatile("st.release.gpu.global.b32 [%0], %1;" ::"l"(&g_flag[((32 + tau) * 8 + cs) * 32]), "r"(ep) : "memory");
#pragma unroll
            for (int n = 0; n < 8; n++) {
                const float2 gv = ldsf2(sb + SM_GB + (8 * n + 2 * q) * 4);
#pragma unroll
                for (int r = 0; r < 2; r++) {
                    acc[4 * n + 2 * r] = fmaf(gv.x, acc[4 * n + 2 * r], blo(x2p[2 * n + r]));
                    acc[4 * n + 2 * r + 1] = fmaf(gv.y, acc[4 * n + 2 * r + 1], bhi(x2p[2 * n + r]));
                }
            }
        }
        asm volatile("setmaxnreg.inc.sync.aligned.u32 232;");
        uint32_t H[56];
        const uint32_t hbuf = sb + SM_Q + (s ? 0 : 4 * 8192) + wt * 16;
        {
            float e[112];
            uint4 p0, p1;
            int slot = (32 + 8 * s) % NSLOT;
#pragma unroll 1
            for (int c = 0; c < 8; c++) {
                mbar_wait(BAR(B_FULL + 32 + 8 * s + c));
                mbar_wait(BAR(B_WFULL + c));
                const uint64_t da = mkdesc(sb + SM_Q + slot * 8192, 16, 1024, 1), db = mkdesc(sb + wstage(c), 4096, 512, 2);
                WG_FENCE();
#pragma unroll
                for (int k = 0; k < 4; k++) wgmma_ss224(e, da + 2 * k, db + 64 * k, (c | k) != 0);
                WG_COMMIT();
                if (c) { WG_WAIT(1); __syncwarp(); if (lane == 0) { mbar_arrive(BAR(B_EMPTY + 32 + 8 * s + c - 1)); mbar_arrive(BAR(B_WEMPTY + c - 1)); } }
                slot = slot == NSLOT - 1 ? 0 : slot + 1;
            }
            p0 = ldr128(&g_stats2[row0 * 8 + 2 * q]); p1 = ldr128(&g_stats2[(row0 + 8) * 8 + 2 * q]);
            float sm[2] = {__uint_as_float(p0.x) + __uint_as_float(p0.z), __uint_as_float(p1.x) + __uint_as_float(p1.z)};
            float sq[2] = {__uint_as_float(p0.y) + __uint_as_float(p0.w), __uint_as_float(p1.y) + __uint_as_float(p1.w)};
            float r3[2], c3[2];
#pragma unroll
            for (int r = 0; r < 2; r++) {
                sm[r] += shx(sm[r], 1); sq[r] += shx(sq[r], 1); sm[r] += shx(sm[r], 2); sq[r] += shx(sq[r], 2);
                const float m = sm[r] * (1.f / 512.f);
                r3[r] = rsqrtf(fmaxf(fmaf(-m, m, sq[r] * (1.f / 512.f)), 0.f) + LN_EPS); c3[r] = -r3[r] * m;
            }
            WG_WAIT(0);
            pin<112>(e);
            __syncwarp();
            if (lane == 0) { mbar_arrive(BAR(B_EMPTY + 32 + 8 * s + 7)); mbar_arrive(BAR(B_WEMPTY + 7)); }
            const uint32_t rbuf = mapa(hbuf, pr ^ 1), rbar = mapa(BAR(B_HFULL + s), pr ^ 1);
#pragma unroll
            for (int k = 0; k < 14; k++) {
#pragma unroll
                for (int h = 0; h < 2; h++) {
                    const float2 u = ldsf2(sb + SM_U4 + (16 * k + 8 * h + 2 * q) * 4);
#pragma unroll
                    for (int r = 0; r < 2; r++)
                        H[4 * k + 2 * h + r] = pack2(gelu(fmaf(r3[r], e[8 * k + 4 * h + 2 * r], c3[r] * u.x)), gelu(fmaf(r3[r], e[8 * k + 4 * h + 2 * r + 1], c3[r] * u.y)));
                }
                if (k == 5) mbar_wait_cluster(BAR(B_HFREE + s));
                if (k >= 5) {
#pragma unroll
                    for (int j = (k == 5 ? 0 : k); j <= k; j++)
                        asm volatile("st.async.weak.shared::cluster.mbarrier::complete_tx::bytes.v4.b32 [%0], {%1,%2,%3,%4}, [%5];"
                                     ::"r"(rbuf + j * 2048), "r"(H[4 * j]), "r"(H[4 * j + 1]), "r"(H[4 * j + 2]), "r"(H[4 * j + 3]), "r"(rbar) : "memory");
                }
            }
        }
        {
            float X[32], Y[32];
            uint32_t Hp[56];
            uint4* pdst = g_part + (size_t)((gi * 8 + 4 * pr) * 6 + s) * 512 + wt;
#define TILE(D, A, qq, first) { mbar_wait(BAR(B_WFULL + (qq))); const uint64_t db = mkdesc(sb + wstage(qq), 8192, 1024, 1); WG_FENCE(); \
            _Pragma("unroll") for (int k = 0; k < 14; k++) wgmma_rs64(D, A[4 * k], A[4 * k + 1], A[4 * k + 2], A[4 * k + 3], db + 128 * k, !(first) || k != 0); \
            WG_COMMIT(); }
#define REL(qq) { WG_WAIT(1); if ((qq) < 12) warp_arrive(BAR(B_WEMPTY + (qq))); }
#define SEND(D, st_) { pin<32>(D); uint4* pd = pdst + (((pa + (st_)) & 3) * 6 + 2 * ((st_) - 1)) * 512; \
            _Pragma("unroll") for (int v = 0; v < 4; v++) str128(pd + 128 * v, make_uint4(pack2(D[8 * v], D[8 * v + 1]), pack2(D[8 * v + 2], D[8 * v + 3]), pack2(D[8 * v + 4], D[8 * v + 5]), pack2(D[8 * v + 6], D[8 * v + 7]))); }
            pinu<56>(H);
            TILE(X, H, 8, true)
            TILE(Y, H, 9, true) REL(8)
            mbar_wait_cluster(BAR(B_HFULL + s));
#pragma unroll
            for (int k = 0; k < 14; k++) { const uint4 v = lds128(hbuf + k * 2048); Hp[4 * k] = v.x; Hp[4 * k + 1] = v.y; Hp[4 * k + 2] = v.z; Hp[4 * k + 3] = v.w; }
            pinu<56>(Hp);
            TILE(X, Hp, 10, false) REL(9)
            TILE(Y, Hp, 11, false) REL(10)
            SEND(X, 1)
            TILE(X, H, 12, true) REL(11)
            SEND(Y, 2)
            TILE(X, Hp, 13, false)
            TILE(Y, H, 14, true) REL(13)
            SEND(X, 3)
            TILE(Y, Hp, 15, false) REL(14)
            const uint4* psrc = pdst + pa * 6 * 512;
            uint4 pv[12];
            int it = 0;
            bool ok;
            do {
                ok = true;
#pragma unroll
                for (int i = 0; i < 12; i++) pv[i] = ldr128(psrc + (i >> 2) * 1024 + (i & 3) * 128);
#pragma unroll
                for (int i = 0; i < 12; i++) ok = ok && valid4(pv[i]);
                if (++it > SPIN_MAX) __trap();
            } while (!ok);
#pragma unroll
            for (int v = 0; v < 4; v++) {
                const uint32_t a[4] = {pv[v].x, pv[v].y, pv[v].z, pv[v].w}, c[4] = {pv[4 + v].x, pv[4 + v].y, pv[4 + v].z, pv[4 + v].w},
                               d[4] = {pv[8 + v].x, pv[8 + v].y, pv[8 + v].z, pv[8 + v].w};
#pragma unroll
                for (int i = 0; i < 4; i++) {
                    X[8 * v + 2 * i] = blo(a[i]) + blo(c[i]) + blo(d[i]);
                    X[8 * v + 2 * i + 1] = bhi(a[i]) + bhi(c[i]) + bhi(d[i]);
                }
            }
            WG_WAIT(0);
            pin<32>(Y);
            const uint32_t stg = sb + SM_Q + 8 * 8192 + warp * 2048;
            const int srow = (lane & 7) + 8 * ((lane >> 3) & 1);
#pragma unroll
            for (int n2 = 0; n2 < 4; n2++) {
                uint32_t o[4];
#pragma unroll
                for (int h = 0; h < 2; h++) {
                    const int n = 2 * n2 + h;
                    const float2 gv = ldsf2(sb + SM_GB + (8 * n + 2 * q) * 4);
#pragma unroll
                    for (int r = 0; r < 2; r++)
                        o[2 * h + r] = pack2(fmaf(gv.x, X[4 * n + 2 * r] + Y[4 * n + 2 * r], acc[4 * n + 2 * r]),
                                             fmaf(gv.y, X[4 * n + 2 * r + 1] + Y[4 * n + 2 * r + 1], acc[4 * n + 2 * r + 1]));
                }
                stsm4(stg + srow * 128 + (((2 * n2 + (lane >> 4)) ^ (lane & 7)) << 4), o[0], o[1], o[2], o[3]);
            }
            __syncwarp();
            bf16* oo = P.out + (size_t)(64 * tau + 16 * w4 + (lane >> 3)) * 512 + 64 * cs + 8 * (lane & 7);
#pragma unroll
            for (int i = 0; i < 4; i++) {
                const int r = 4 * i + (lane >> 3);
                const uint4 v = lds128(stg + r * 128 + (((lane & 7) ^ (r & 7)) << 4));
                stg128(oo + i * 2048, v.x, v.y, v.z, v.w);
            }
            if (tid == 128) str32(&g_epoch[b], ep);
#undef TILE
#undef REL
#undef SEND
        }
    } else {
        const int at = tid - 256, aw = warp - 8;
        uint4 xr[4][2];
#pragma unroll
        for (int r = 0; r < 4; r++) {
            const bf16* p = P.x + (size_t)(16 * b + 4 * aw + r) * 512 + 8 * lane;
            xr[r][0] = ldg128(p); xr[r][1] = ldg128(p + 256);
        }
        float sc[4];
#pragma unroll
        for (int r = 0; r < 4; r++) sc[r] = __bfloat162float(P.c[at + 128 * r]);
        const bf16* wm = P.wmod + (size_t)at * 3072 + 4 * b;
        uint2 wv[4][2];
#pragma unroll
        for (int r = 0; r < 4; r++) { wv[r][0] = ldg64(wm + (size_t)r * 128 * 3072); wv[r][1] = ldg64(wm + (size_t)r * 128 * 3072 + 512); }
        const uint32_t ep = ldr32(&g_epoch[b]) + 1;
        for (int i = at; i < B_COUNT; i += 128) {
            int cnt = 1;
            if ((i >= B_EMPTY && i < B_WFULL) || (i >= B_W1SC && i < B_W1FREE) || i >= B_FAR) cnt = 4;
            if ((i >= B_WEMPTY && i < B_W1FULL) || i == B_W1FREE || i == B_W2FREE) cnt = 8;
            mbar_init(BAR(i), cnt);
            if (i == B_HFULL || i == B_HFULL + 1) mbar_expect(BAR(i), 28672);
        }
        asm volatile("fence.mbarrier_init.release.cluster;" ::: "memory");
        asm volatile("bar.arrive 5, 384;" ::: "memory");
        if (at < 7) {
            const CUtensorMap* m = at == 0 ? &tmX2 : at == 1 ? &tmG : at == 2 ? &tmX1 : at == 3 ? &tmW1 : at == 4 ? &tmW2 : at == 5 ? &tmW3 : &tmW4;
            asm volatile("prefetch.tensormap [%0];" ::"l"(m) : "memory");
        }
        {
            const uint4 e4 = make_uint4(SENT, SENT, SENT, SENT);
            if (at < 16) str128(&g_stats1[1024 * (at >> 3) + 64 * gi + 8 * cs + (at & 7)], e4);
            else if (at < 19) str128(&g_u123[512 * (at - 16) + 64 * cs + 4 * gi], e4);
            else if (at < 23 && b < 112) str128(&g_u4[16 * b + 4 * (at - 19)], e4);
        }
        {
            float mean[4], var[4];
#pragma unroll
            for (int r = 0; r < 4; r++) {
                float a = 0.f;
#pragma unroll
                for (int h = 0; h < 2; h++)
                    a += (blo(xr[r][h].x) + bhi(xr[r][h].x)) + (blo(xr[r][h].y) + bhi(xr[r][h].y)) + (blo(xr[r][h].z) + bhi(xr[r][h].z)) + (blo(xr[r][h].w) + bhi(xr[r][h].w));
                mean[r] = a;
            }
#pragma unroll
            for (int m = 16; m; m >>= 1)
#pragma unroll
                for (int r = 0; r < 4; r++) mean[r] += shx(mean[r], m);
#pragma unroll
            for (int r = 0; r < 4; r++) {
                mean[r] *= 1.f / 512.f;
                float a = 0.f, c = 0.f;
#pragma unroll
                for (int h = 0; h < 2; h++) {
                    const uint32_t wd[4] = {xr[r][h].x, xr[r][h].y, xr[r][h].z, xr[r][h].w};
#pragma unroll
                    for (int i = 0; i < 4; i++) { const float d0 = blo(wd[i]) - mean[r], d1 = bhi(wd[i]) - mean[r]; a = fmaf(d0, d0, a); c = fmaf(d1, d1, c); }
                }
                var[r] = a + c;
            }
            halve<4>(var, 16, lane & 16); halve<2>(var, 8, lane & 8);
            var[0] += shx(var[0], 4); var[0] += shx(var[0], 2); var[0] += shx(var[0], 1);
            const int r = lane >> 3;
            const float m = r == 0 ? mean[0] : r == 1 ? mean[1] : r == 2 ? mean[2] : mean[3];
            if ((lane & 7) == 0) str64(&g_stats0[16 * b + 4 * aw + r], ~__float_as_uint(m), ~__float_as_uint(rsqrtf(var[0] * (1.f / 512.f) + LN_EPS)));
        }
        {
            uint4* pdst = g_part + (size_t)((gi * 8 + 4 * pr) * 6) * 512 + at;
#pragma unroll
            for (int st_ = 1; st_ < 4; st_++)
#pragma unroll
                for (int v = 0; v < 8; v++) stg128(pdst + (((pa + st_) & 3) * 6 + 2 * (st_ - 1)) * 512 + 128 * v, SENT, SENT, SENT, SENT);
        }
#pragma unroll
        for (int r = 0; r < 4; r++) sc[r] = bround(sc[r] / (1.f + __expf(-sc[r])));
        uint2 wu[4][4];
        {
            float v[8];
#pragma unroll
            for (int k = 0; k < 2; k++) {
                v[4 * k] = v[4 * k + 1] = v[4 * k + 2] = v[4 * k + 3] = 0.f;
#pragma unroll
                for (int r = 0; r < 4; r++) {
                    v[4 * k] = fmaf(sc[r], blo(wv[r][k].x), v[4 * k]); v[4 * k + 1] = fmaf(sc[r], bhi(wv[r][k].x), v[4 * k + 1]);
                    v[4 * k + 2] = fmaf(sc[r], blo(wv[r][k].y), v[4 * k + 2]); v[4 * k + 3] = fmaf(sc[r], bhi(wv[r][k].y), v[4 * k + 3]);
                }
            }
#pragma unroll
            for (int r = 0; r < 4; r++)
#pragma unroll
                for (int k = 0; k < 4; k++) wu[r][k] = ldg64(wm + (size_t)r * 128 * 3072 + 1024 + 512 * k);
            if (at == 0) l2_prefetch(P.w1 + (size_t)b * 2048, 4096);
            float t = bround(aux_reduce<8>(v, sb + SM_ARED, at));
            if (at < 8) stsf(sb + SM_OWN + 4 * at, at < 4 ? t : bround(1.f + t));
            if (aw == 0) { warp_arrive(BAR(B_MOD)); }
        }
        asm volatile("setmaxnreg.dec.sync.aligned.u32 72;");
        {
            float v[16];
#pragma unroll
            for (int k = 0; k < 4; k++) {
                v[4 * k] = v[4 * k + 1] = v[4 * k + 2] = v[4 * k + 3] = 0.f;
#pragma unroll
                for (int r = 0; r < 4; r++) {
                    v[4 * k] = fmaf(sc[r], blo(wu[r][k].x), v[4 * k]); v[4 * k + 1] = fmaf(sc[r], bhi(wu[r][k].x), v[4 * k + 1]);
                    v[4 * k + 2] = fmaf(sc[r], blo(wu[r][k].y), v[4 * k + 2]); v[4 * k + 3] = fmaf(sc[r], bhi(wu[r][k].y), v[4 * k + 3]);
                }
            }
            float t = bround(aux_reduce<16>(v, sb + SM_ARED + 256, at));
            if (aw == 0) {
                if ((lane >> 2) == 2) t = 1.f + t;
                const float t1 = __shfl_down_sync(0xffffffffu, t, 1);
                if (lane < 4) stsf(sb + SM_OWN + 32 + 4 * lane, t);
                else if (lane < 16 && !(lane & 1)) str32(&g_modp[256 * ((lane >> 2) - 1) + 2 * b + ((lane >> 1) & 1)], ~pack2(t, t1));
                warp_arrive(BAR(B_MOD + 1));
            }
        }
        if (at == 0) { l2_prefetch(P.w2 + (size_t)b * 2048, 4096); }
        {
            float v[16];
#pragma unroll
            for (int i = 0; i < 16; i++) v[i] = 0.f;
            if (b < 112) {
                uint4 w[4][2];
#pragma unroll
                for (int r = 0; r < 4; r++) { const bf16* p = P.w3 + (size_t)(at + 128 * r) * 1792 + 16 * b; w[r][0] = ldg128(p); w[r][1] = ldg128(p + 8); }
#pragma unroll
                for (int r = 0; r < 4; r++)
#pragma unroll
                    for (int h = 0; h < 2; h++) {
                        v[8 * h] += blo(w[r][h].x); v[8 * h + 1] += bhi(w[r][h].x); v[8 * h + 2] += blo(w[r][h].y); v[8 * h + 3] += bhi(w[r][h].y);
                        v[8 * h + 4] += blo(w[r][h].z); v[8 * h + 5] += bhi(w[r][h].z); v[8 * h + 6] += blo(w[r][h].w); v[8 * h + 7] += bhi(w[r][h].w);
                    }
            }
            if (at == 0) l2_prefetch(P.w4 + (size_t)b * 7168, 14336);
            const float t = aux_reduce<16>(v, sb + SM_ARED, at);
            if (at < 16 && b < 112) str32(&g_u4[16 * b + at], __float_as_uint(t));
        }
        {
            uint2 vs, vc; uint32_t vg; int it = 0;
            do {
                vs = ldr64(&g_modp[2 * at]); vc = ldr64(&g_modp[256 + 2 * at]); vg = ldr32(&g_modp[512 + 32 * cs + lane]);
                if (++it > SPIN_MAX) __trap();
            } while (!vs.x || !vs.y || !vc.x || !vc.y || !vg);
            const float sv[4] = {blo(~vs.x), bhi(~vs.x), blo(~vs.y), bhi(~vs.y)}, cv[4] = {blo(~vc.x), bhi(~vc.x), blo(~vc.y), bhi(~vc.y)};
            sts128(sb + SM_CS + at * 32, make_uint4(__float_as_uint(cv[0]), __float_as_uint(sv[0]), __float_as_uint(cv[1]), __float_as_uint(sv[1])));
            sts128(sb + SM_CS + at * 32 + 16, make_uint4(__float_as_uint(cv[2]), __float_as_uint(sv[2]), __float_as_uint(cv[3]), __float_as_uint(sv[3])));
            if (aw == 0) sts64(sb + SM_GB + lane * 8, __float_as_uint(blo(~vg)), __float_as_uint(bhi(~vg)));
            float v[8] = {0.f, 0.f, 0.f, 0.f, 0.f, 0.f, 0.f, 0.f};
#pragma unroll
            for (int i = 0; i < 4; i++) {
                v[0] += cv[i]; v[1] += sv[i]; v[2] = fmaf(cv[i], cv[i], v[2]); v[3] = fmaf(cv[i], sv[i], v[3]); v[4] = fmaf(sv[i], sv[i], v[4]);
            }
            const float t = aux_reduce<8>(v, sb + SM_ARED + 256, at);
            if (at < 5) stsf(sb + SM_CONST + 4 * at, t);
        }
        {
            mbar_wait(BAR(B_W1FULL));
            float v[16];
#pragma unroll
            for (int i = 0; i < 16; i++) v[i] = 0.f;
#pragma unroll 1
            for (int r = 0; r < 4; r++) {
                const int k = at + 128 * r;
                const float2 cv = ldsf2(sb + SM_CS + k * 8);
                const uint32_t c2 = pack2(cv.x, cv.x), ra = sb + SM_W1 + k * 128;
                const uint2 o = lds64(ra + (((gi >> 1) ^ (k & 7)) << 4) + (gi & 1) * 8);
                const uint32_t n0 = hmul2(o.x, c2), n1 = hmul2(o.y, c2);
                v[0] += blo(n0); v[1] += bhi(n0); v[2] += blo(n1); v[3] += bhi(n1);
                v[4] = fmaf(cv.y, blo(o.x), v[4]); v[5] = fmaf(cv.y, bhi(o.x), v[5]); v[6] = fmaf(cv.y, blo(o.y), v[6]); v[7] = fmaf(cv.y, bhi(o.y), v[7]);
                v[8] += blo(o.x); v[9] += bhi(o.x); v[10] += blo(o.y); v[11] += bhi(o.y);
#pragma unroll
                for (int j = 0; j < 8; j++) {
                    const uint32_t a = ra + ((j ^ (k & 7)) << 4);
                    uint4 w = lds128(a);
                    w.x = hmul2(w.x, c2); w.y = hmul2(w.y, c2); w.z = hmul2(w.z, c2); w.w = hmul2(w.w, c2);
                    sts128(a, w);
                }
            }
            fence_async_smem();
            const float t = aux_reduce<16>(v, sb + SM_ARED, at);
            if (at < 12) str32(&g_u123[512 * (at >> 2) + 64 * cs + 4 * gi + (at & 3)], __float_as_uint(t));
            warp_arrive(BAR(B_W1SC));
        }
        asm volatile("setmaxnreg.dec.sync.aligned.u32 40;");
        if (aw < 2) {
            const int s = aw, tau = 16 * s + gi, c = lane & 7;
            const int sh = (c & 4 ? 2 : 1) * (c & 2 ? 1 : -1);
            mbar_wait(BAR(B_CONV + s));
#pragma unroll 1
            for (int ph = 0; ph < 3; ph++) {
                const uint32_t* fp; uint32_t target = ep; bool need = lane < 8;
                if (ph == 0) { fp = &g_cnt[((tau < 18 ? 0 : 8) + c) * 32]; target = 16 * ep; }
                else if (ph == 1) {
                    const int tn = lane < 8 ? tau : tau + (sh > 0 ? 1 : -1);
                    need = lane < 16 && tn >= 0 && tn < 32;
                    fp = &g_flag[((need ? tn : tau) * 8 + c) * 32];
                } else fp = &g_flag[((32 + tau) * 8 + c) * 32];
                const CUtensorMap* tm = ph == 0 ? &tmX2 : ph == 1 ? &tmG : &tmX1;
                const int n0 = 16 * ph + 8 * s;
                int done = 0, it = 0, slot = n0 % NSLOT;
                while (done < 8) {
                    bool rdy = true;
                    if (need) { rdy = (int)(lda32(fp) - target) >= 0; need = !rdy; }
                    uint32_t m = __ballot_sync(0xffffffffu, rdy);
                    m &= m >> 8;
                    if ((m >> done) & 1) {
                        fence_async_all();
                        do {
                            const int shc = __shfl_sync(0xffffffffu, sh, done);
                            if (lane == 0) {
                                const int n = n0 + done;
                                if (n >= NSLOT) mbar_wait(BAR(B_EMPTY + n - NSLOT));
                                mbar_expect(BAR(B_FULL + n), 8192);
                                const int c0 = ph == 0 ? 64 * tau : 64 * done, c1 = ph == 0 ? 64 * done : 64 * tau + (ph == 1 ? shc : 0);
                                tma2d(sb + SM_Q + slot * 8192, tm, c0, c1, BAR(B_FULL + n));
                            }
                            __syncwarp();
                            done++; slot = slot == NSLOT - 1 ? 0 : slot + 1;
                        } while (done < 8 && ((m >> done) & 1));
                    }
                    if (++it > SPIN_MAX) __trap();
                }
                if (ph == 0 && s == 0 && lane == 0) mbar_arrive(BAR(B_SEEN));
            }
            if (lane == 0) {
                mbar_wait(BAR(B_EMPTY + 39 + 8 * s));
                if (s == 0) mbar_wait(BAR(B_EMPTY + 40));
                mbar_arrive_remote(mapa(BAR(B_HFREE + s), pr ^ 1));
            }
        } else if (aw == 2) {
            if (lane == 0) {
                mbar_wait(BAR(B_CONV + 1));
                fence_async_smem();
                mbar_expect(BAR(B_W2FULL), 65536);
                tma5d(sb + SM_W2, &tmW2, 64 * cs, 0, 0, 0, 0, BAR(B_W2FULL));
#pragma unroll 1
                for (int t = 0; t < 16; t++) {
                    mbar_wait(BAR(t < 2 ? B_W1FREE : t < 4 ? B_W2FREE : B_WEMPTY + t - 4));
                    mbar_expect(BAR(B_WFULL + t), 28672);
                    if (t < 8) tma5d(sb + wstage(t), &tmW3, 0, 0, 8 * t, 0, 7 * fs, BAR(B_WFULL + t));
                    else {
                        const int j = t - 8;
                        const int st_ = j < 4 ? 1 + (j & 1) : j < 6 ? 3 : 0, peer = j < 4 ? j >> 1 : j & 1;
                        tma2d(sb + wstage(t), &tmW4, 64 * (4 * pr + ((pa + st_) & 3)), 224 * (fs ^ peer), BAR(B_WFULL + t));
                    }
                }
            }
        } else {
#pragma unroll 1
            for (int k = 0; k < 2; k++) {
                if (lane == 0) {
                    mbar_wait(BAR(B_CONV + k));
                    asm volatile("red.release.gpu.global.add.u32 [%0], 1;" ::"l"(&g_cnt[(8 * k + (b >> 4)) * 32]) : "memory");
                }
                __syncwarp();
            }
            mbar_wait(BAR(B_SEEN));
#pragma unroll 1
            for (int i = lane; i < 104; i += 32) {
                const uint32_t* src = i < 48 ? &g_u123[512 * (i >> 4) + 64 * cs + 4 * (i & 15)] : &g_u4[224 * fs + 4 * (i - 48)];
                uint4 v; int it = 0;
                do { v = ldr128(src); if (++it > SPIN_MAX) __trap(); } while (!valid4(v));
                sts128(sb + (i < 48 ? SM_U123 + 16 * i : SM_U4 + 16 * (i - 48)), v);
            }
            warp_arrive(BAR(B_UREADY));
            if (lane < 8) {
                int it = 0;
                while ((int)(lda32(&g_cnt[(8 + lane) * 32]) - 16 * ep) < 0) if (++it > SPIN_MAX) __trap();
            }
            __syncwarp();
            if (lane < 16) str64(&g_stats0[16 * b + lane], 0, 0);
            else if (lane < 19) str64(&g_modp[256 * (lane - 16) + 2 * b], 0, 0);
        }
    }
}

typedef CUresult (*EncodeFn)(CUtensorMap*, CUtensorMapDataType, cuuint32_t, void*, const cuuint64_t*, const cuuint64_t*,
                             const cuuint32_t*, const cuuint32_t*, CUtensorMapInterleave, CUtensorMapSwizzle,
                             CUtensorMapL2promotion, CUtensorMapFloatOOBfill);

void encode(EncodeFn fn, CUtensorMap* m, const void* base, int rank, const cuuint64_t* dim, const cuuint64_t* stride,
            const cuuint32_t* box, CUtensorMapSwizzle sw) {
    const cuuint32_t es[5] = {1, 1, 1, 1, 1};
    fn(m, CU_TENSOR_MAP_DATA_TYPE_BFLOAT16, rank, const_cast<void*>(base), dim, stride, box, es, CU_TENSOR_MAP_INTERLEAVE_NONE,
       sw, CU_TENSOR_MAP_L2_PROMOTION_L2_128B, CU_TENSOR_MAP_FLOAT_OOB_FILL_NONE);
}

}

extern "C" void kernel_launch(void* const* d_in, const int* in_sizes, int n_in, void* d_out, int out_size) {
    (void)in_sizes; (void)n_in; (void)out_size;
    Params P;
    P.x = (const bf16*)d_in[0]; P.Are = (const bf16*)d_in[1]; P.Aim = (const bf16*)d_in[2]; P.Bre = (const bf16*)d_in[3];
    P.Bim = (const bf16*)d_in[4]; P.Cre = (const bf16*)d_in[5]; P.Cim = (const bf16*)d_in[6]; P.logdt = (const bf16*)d_in[7];
    P.dskip = (const bf16*)d_in[8]; P.w1 = (const bf16*)d_in[10]; P.w2 = (const bf16*)d_in[11]; P.w3 = (const bf16*)d_in[12];
    P.w4 = (const bf16*)d_in[13]; P.c = (const bf16*)d_in[14]; P.wmod = (const bf16*)d_in[15]; P.out = (bf16*)d_out;

    void* fnp = nullptr;
    cudaDriverEntryPointQueryResult qr;
    cudaGetDriverEntryPoint("cuTensorMapEncodeTiled", &fnp, cudaEnableDefault, &qr);
    EncodeFn fn = (EncodeFn)fnp;
    cudaFuncSetAttribute(fused_kernel, cudaFuncAttributeMaxDynamicSharedMemorySize, SM_TOTAL);
    void *px2, *pg, *px1;
    cudaGetSymbolAddress(&px2, g_x2t); cudaGetSymbolAddress(&pg, g_g); cudaGetSymbolAddress(&px1, g_x1);
    CUtensorMap tmX2, tmG, tmX1, tmW1, tmW2, tmW3, tmW4;
    { const cuuint64_t d[2] = {2048, 512}, st[1] = {4096}; const cuuint32_t bx[2] = {64, 64}; encode(fn, &tmX2, px2, 2, d, st, bx, CU_TENSOR_MAP_SWIZZLE_128B); }
    { const cuuint64_t d[2] = {512, 2048}, st[1] = {1024}; const cuuint32_t bx[2] = {64, 64};
      encode(fn, &tmG, pg, 2, d, st, bx, CU_TENSOR_MAP_SWIZZLE_128B); encode(fn, &tmX1, px1, 2, d, st, bx, CU_TENSOR_MAP_SWIZZLE_128B); }
    { const cuuint64_t d[2] = {512, 512}, st[1] = {1024}; const cuuint32_t bx[2] = {64, 256}; encode(fn, &tmW1, P.w1, 2, d, st, bx, CU_TENSOR_MAP_SWIZZLE_128B); }
    { const cuuint64_t d[5] = {512, 2, 8, 4, 8}, st[4] = {1024, 8192, 2048, 65536}; const cuuint32_t bx[5] = {64, 2, 8, 4, 8};
      encode(fn, &tmW2, P.w2, 5, d, st, bx, CU_TENSOR_MAP_SWIZZLE_128B); }
    { const cuuint64_t d[5] = {32, 2, 64, 4, 56}, st[4] = {3584, 8 * 3584, 2 * 3584, 64}; const cuuint32_t bx[5] = {32, 2, 8, 4, 7};
      encode(fn, &tmW3, P.w3, 5, d, st, bx, CU_TENSOR_MAP_SWIZZLE_64B); }
    { const cuuint64_t d[2] = {512, 1792}, st[1] = {1024}; const cuuint32_t bx[2] = {64, 224}; encode(fn, &tmW4, P.w4, 2, d, st, bx, CU_TENSOR_MAP_SWIZZLE_128B); }

    cudaLaunchConfig_t cfg = {};
    cfg.gridDim = dim3(128); cfg.blockDim = dim3(384); cfg.dynamicSmemBytes = SM_TOTAL; cfg.stream = cudaStreamPerThread;
    cudaLaunchAttribute at[1];
    at[0].id = cudaLaunchAttributeClusterDimension; at[0].val.clusterDim.x = 2; at[0].val.clusterDim.y = 1; at[0].val.clusterDim.z = 1;
    cfg.attrs = at; cfg.numAttrs = 1;
    cudaLaunchKernelEx(&cfg, fused_kernel, P, tmX2, tmG, tmX1, tmW1, tmW2, tmW3, tmW4);
}
```

```cpp
#include <cuda_runtime.h>
#include <cuda_bf16.h>
#include <cuda.h>
#include <stdint.h>

namespace {

typedef __nv_bfloat16 bf16;

constexpr int SM_W1 = 0, SM_W2 = 65536, SM_Q = 131072, NSLOT = 11, SM_MISC = SM_Q + NSLOT * 8192;
constexpr int UW_B = 10912, SM_UW = SM_W2, XS_B = 10240, SM_XS = SM_UW + 4 * UW_B;
constexpr int WD_B = 3104, SM_WD = SM_Q;
constexpr int SM_SCV = SM_WD + 4 * WD_B, SM_CBV = SM_SCV + 512, SM_SBV = SM_CBV + 1024, SM_ONE = SM_SBV + 1024;
constexpr int SM_W3C = SM_Q + 2 * 8192, SM_WM = SM_Q + 4 * 8192, SM_XC = SM_Q + 7 * 8192, SM_DEP = SM_XC;
constexpr int PT_PITCH = 272, PT_B = 24 * PT_PITCH + 1024;
constexpr int SM_BAR = SM_MISC;
constexpr int SM_CS = SM_BAR + 1408;
constexpr int SM_U123 = SM_CS + 4096;
constexpr int SM_GB = SM_U123 + 2048;
constexpr int SM_RED = SM_GB + 256;
constexpr int SM_U4 = SM_W1 + 57344;
constexpr int SM_ARED = SM_RED + 1536;
constexpr int SM_OWN = SM_ARED + 640;
constexpr int SM_CONST = SM_OWN + 64;
constexpr int SM_TS = SM_CONST + 64;
constexpr int SM_TOTAL = SM_TS + 384;
static_assert(SM_XS + 2 * XS_B <= SM_Q, "conv buffers");
static_assert(SM_TOTAL <= 232448, "smem");
constexpr int T0o = 8, T4o = 288, T2o = 432, TM2o = 512, T1o = 592, T3o = 640, T5o = 688, TM1o = 736;
constexpr int B_WM = 0  , B_XC = 3  , B_W3C = 5, B_EARLY = 6,
              B_FULL = 6  ,
              B_WFULL = 54  , B_HFULL = 70  , B_W1FULL = 72, B_W2FULL = 73, B_MOD = 74  ,
              B_HFREE = 76  , B_U = 78  , B_WEMPTY = 80  , B_W1FREE = 92, B_W2FREE = 93, B_DONE = 94,
              B_CONV = 95  , B_W1SC = 97, B_W1RDY = 98,
              B_NEAR = 99  , B_EMPTY = 115  ;

constexpr float LN_EPS = 1e-5f;
constexpr int SPIN_MAX = 1 << 20;

struct Scratch {
    bf16 x2t[512 * 2048], g[2048 * 512], x1[2048 * 512];
    uint4 part[16 * 8 * 3 * 2 * 512];
    uint4 stats1[2048];
    float2 stats2[2048 * 8];
    uint2 stats0[2048];
    uint32_t modq[8 * 3072];
    uint4 modp[128 * 4];
    uint32_t u123[3 * 512], u4[1792];
    uint32_t cnt[2 * 8 * 32], flag[2 * 32 * 8 * 32], epoch[128];
};
__device__ __align__(1024) Scratch G;

struct Params {
    const bf16 *x, *Are, *Aim, *Bre, *Bim, *Cre, *Cim, *logdt, *dskip, *w1, *w2, *w3, *w4, *c, *wmod;
    bf16* out;
};

enum { tmX2, tmG, tmX1, tmWm, tmXc, tmW3c, tmW1, tmW2, tmW3, tmW4, tmCount };
struct Maps { CUtensorMap m[tmCount]; };

__device__ __forceinline__ void mbar_init(uint32_t b, int c) { asm volatile("mbarrier.init.shared::cta.b64 [%0], %1;" ::"r"(b), "r"(c) : "memory"); }
__device__ __forceinline__ void mbar_expect(uint32_t b, int bytes) { asm volatile("mbarrier.arrive.expect_tx.shared::cta.b64 _, [%0], %1;" ::"r"(b), "r"(bytes) : "memory"); }
__device__ __forceinline__ void mbar_arrive(uint32_t b) { asm volatile("mbarrier.arrive.shared::cta.b64 _, [%0];" ::"r"(b) : "memory"); }
__device__ __forceinline__ void mbar_arrive_remote(uint32_t b) { asm volatile("mbarrier.arrive.relaxed.cluster.shared::cluster.b64 _, [%0];" ::"r"(b) : "memory"); }
__device__ __forceinline__ bool mbar_test(uint32_t b) {
    uint32_t ok;
    asm volatile("{.reg .pred p; mbarrier.test_wait.parity.shared::cta.b64 p, [%1], 0; selp.u32 %0, 1, 0, p;}" : "=r"(ok) : "r"(b) : "memory");
    return ok;
}
__device__ __forceinline__ void mbar_wait(uint32_t b) {
    asm volatile("{.reg .pred p; W: mbarrier.try_wait.parity.shared::cta.b64 p, [%0], 0; @!p bra W;}" ::"r"(b) : "memory");
}
__device__ __forceinline__ void mbar_wait_cluster(uint32_t b) {
    asm volatile("{.reg .pred p; W: mbarrier.try_wait.parity.acquire.cluster.shared::cta.b64 p, [%0], 0; @!p bra W;}" ::"r"(b) : "memory");
}
__device__ __forceinline__ void mbar_wait_b(uint32_t b) {
    uint32_t ok; int it = 0;
    do {
        asm volatile("{.reg .pred p; mbarrier.try_wait.parity.shared::cta.b64 p, [%1], 0; selp.u32 %0, 1, 0, p;}" : "=r"(ok) : "r"(b) : "memory");
        if (++it > SPIN_MAX) __trap();
    } while (!ok);
}
__device__ __forceinline__ bool any(uint32_t bad) { return __any_sync(0xffffffffu, bad & 1); }
__device__ __forceinline__ void warp_arrive(uint32_t b) { __syncwarp(); if ((threadIdx.x & 31) == 0) mbar_arrive(b); }
__device__ __forceinline__ void bar_sync(int id, int n) { asm volatile("bar.sync %0, %1;" ::"r"(id), "r"(n) : "memory"); }
__device__ __forceinline__ void fence_async_smem() { asm volatile("fence.proxy.async.shared::cta;" ::: "memory"); }
__device__ __forceinline__ void fence_acquire() { asm volatile("fence.acquire.gpu;" ::: "memory"); }
__device__ __forceinline__ void fence_async_global() { asm volatile("fence.proxy.async.global;" ::: "memory"); }
__device__ __forceinline__ uint32_t mapa(uint32_t a, uint32_t r) { uint32_t d; asm("mapa.shared::cluster.u32 %0, %1, %2;" : "=r"(d) : "r"(a), "r"(r)); return d; }

__device__ __forceinline__ void tma2d(uint32_t dst, const CUtensorMap* m, int c0, int c1, uint32_t bar) {
    asm volatile("cp.async.bulk.tensor.2d.shared::cluster.global.mbarrier::complete_tx::bytes [%0], [%1, {%3, %4}], [%2];"
                 ::"r"(dst), "l"(m), "r"(bar), "r"(c0), "r"(c1) : "memory");
}
__device__ __forceinline__ void tma2d_pair(uint32_t dst, const CUtensorMap* m, int c0, int c1, uint32_t bar) {
    asm volatile("cp.async.bulk.tensor.2d.shared::cluster.global.mbarrier::complete_tx::bytes.multicast::cluster [%0], [%1, {%3, %4}], [%2], %5;"
                 ::"r"(dst), "l"(m), "r"(bar), "r"(c0), "r"(c1), "h"((unsigned short)3) : "memory");
}
__device__ __forceinline__ void tma5d(uint32_t dst, const CUtensorMap* m, int c0, int c1, int c2, int c3, int c4, uint32_t bar) {
    asm volatile("cp.async.bulk.tensor.5d.shared::cluster.global.mbarrier::complete_tx::bytes [%0], [%1, {%3, %4, %5, %6, %7}], [%2];"
                 ::"r"(dst), "l"(m), "r"(bar), "r"(c0), "r"(c1), "r"(c2), "r"(c3), "r"(c4) : "memory");
}
__device__ __forceinline__ void l2_prefetch(const void* p, int bytes) { asm volatile("cp.async.bulk.prefetch.L2.global [%0], %1;" ::"l"(p), "r"(bytes) : "memory"); }

__device__ __forceinline__ uint32_t lds32(uint32_t a) { uint32_t v; asm volatile("ld.shared.b32 %0, [%1];" : "=r"(v) : "r"(a)); return v; }
__device__ __forceinline__ uint2 lds64(uint32_t a) { uint2 v; asm volatile("ld.shared.v2.b32 {%0,%1}, [%2];" : "=r"(v.x), "=r"(v.y) : "r"(a)); return v; }
__device__ __forceinline__ uint4 lds128(uint32_t a) { uint4 v; asm volatile("ld.shared.v4.b32 {%0,%1,%2,%3}, [%4];" : "=r"(v.x), "=r"(v.y), "=r"(v.z), "=r"(v.w) : "r"(a)); return v; }
__device__ __forceinline__ float ldsf(uint32_t a) { return __uint_as_float(lds32(a)); }
__device__ __forceinline__ float2 ldsf2(uint32_t a) { uint2 v = lds64(a); return make_float2(__uint_as_float(v.x), __uint_as_float(v.y)); }
__device__ __forceinline__ void sts16(uint32_t a, uint32_t v) { asm volatile("st.shared.b16 [%0], %1;" ::"r"(a), "h"((unsigned short)v) : "memory"); }
__device__ __forceinline__ void sts32(uint32_t a, uint32_t v) { asm volatile("st.shared.b32 [%0], %1;" ::"r"(a), "r"(v) : "memory"); }
__device__ __forceinline__ void stsf(uint32_t a, float v) { sts32(a, __float_as_uint(v)); }
__device__ __forceinline__ void sts64(uint32_t a, uint32_t x, uint32_t y) { asm volatile("st.shared.v2.b32 [%0], {%1,%2};" ::"r"(a), "r"(x), "r"(y) : "memory"); }
__device__ __forceinline__ void sts128(uint32_t a, uint4 v) { asm volatile("st.shared.v4.b32 [%0], {%1,%2,%3,%4};" ::"r"(a), "r"(v.x), "r"(v.y), "r"(v.z), "r"(v.w) : "memory"); }
__device__ __forceinline__ void ldsm4(uint32_t* r, uint32_t a) { asm volatile("ldmatrix.sync.aligned.m8n8.x4.shared.b16 {%0,%1,%2,%3}, [%4];" : "=r"(r[0]), "=r"(r[1]), "=r"(r[2]), "=r"(r[3]) : "r"(a)); }
__device__ __forceinline__ void ldsm4t(uint32_t* r, uint32_t a) { asm volatile("ldmatrix.sync.aligned.m8n8.x4.trans.shared.b16 {%0,%1,%2,%3}, [%4];" : "=r"(r[0]), "=r"(r[1]), "=r"(r[2]), "=r"(r[3]) : "r"(a)); }
__device__ __forceinline__ void stsm4(uint32_t a, uint32_t r0, uint32_t r1, uint32_t r2, uint32_t r3) { asm volatile("stmatrix.sync.aligned.m8n8.x4.shared.b16 [%0], {%1,%2,%3,%4};" ::"r"(a), "r"(r0), "r"(r1), "r"(r2), "r"(r3) : "memory"); }

__device__ __forceinline__ uint32_t ldg32(const void* p) { uint32_t v; asm volatile("ld.global.nc.b32 %0, [%1];" : "=r"(v) : "l"(p)); return v; }
__device__ __forceinline__ uint4 ldg128(const void* p) { uint4 v; asm volatile("ld.global.nc.L1::no_allocate.v4.b32 {%0,%1,%2,%3}, [%4];" : "=r"(v.x), "=r"(v.y), "=r"(v.z), "=r"(v.w) : "l"(p)); return v; }
__device__ __forceinline__ uint32_t ldr32(const void* p) { uint32_t v; asm volatile("ld.relaxed.gpu.global.b32 %0, [%1];" : "=r"(v) : "l"(p) : "memory"); return v; }
__device__ __forceinline__ uint2 ldr64(const void* p) { uint2 v; asm volatile("ld.relaxed.gpu.global.v2.b32 {%0,%1}, [%2];" : "=r"(v.x), "=r"(v.y) : "l"(p) : "memory"); return v; }
__device__ __forceinline__ uint4 ldr128(const void* p) { uint4 v; asm volatile("ld.relaxed.gpu.global.v4.b32 {%0,%1,%2,%3}, [%4];" : "=r"(v.x), "=r"(v.y), "=r"(v.z), "=r"(v.w) : "l"(p) : "memory"); return v; }
__device__ __forceinline__ void str32(void* p, uint32_t v) { asm volatile("st.relaxed.gpu.global.b32 [%0], %1;" ::"l"(p), "r"(v) : "memory"); }
__device__ __forceinline__ void str64(void* p, uint32_t x, uint32_t y) { asm volatile("st.relaxed.gpu.global.v2.b32 [%0], {%1,%2};" ::"l"(p), "r"(x), "r"(y) : "memory"); }
__device__ __forceinline__ void str128(void* p, uint4 v) { asm volatile("st.relaxed.gpu.global.v4.b32 [%0], {%1,%2,%3,%4};" ::"l"(p), "r"(v.x), "r"(v.y), "r"(v.z), "r"(v.w) : "memory"); }
__device__ __forceinline__ void stg32(void* p, uint32_t v) { asm volatile("st.global.b32 [%0], %1;" ::"l"(p), "r"(v) : "memory"); }
__device__ __forceinline__ void stg128(void* p, uint32_t x, uint32_t y, uint32_t z, uint32_t w) { asm volatile("st.global.v4.b32 [%0], {%1,%2,%3,%4};" ::"l"(p), "r"(x), "r"(y), "r"(z), "r"(w) : "memory"); }
__device__ __forceinline__ uint32_t tagw(uint32_t w, uint32_t ep) { return (w & ~1u) | (ep & 1u); }
__device__ __forceinline__ uint32_t tagf(float f, uint32_t ep) { return tagw(__float_as_uint(f), ep); }
__device__ __forceinline__ uint32_t stale2(uint2 v, uint32_t ep) { return (v.x ^ ep) | (v.y ^ ep); }
__device__ __forceinline__ uint32_t stale4(uint4 v, uint32_t ep) { return ((v.x ^ ep) | (v.y ^ ep)) | ((v.z ^ ep) | (v.w ^ ep)); }

__device__ __forceinline__ uint32_t pack2(float lo, float hi) { uint32_t r; asm("cvt.rn.bf16x2.f32 %0, %1, %2;" : "=r"(r) : "f"(hi), "f"(lo)); return r; }
__device__ __forceinline__ float blo(uint32_t v) { return __uint_as_float(v << 16); }
__device__ __forceinline__ float bhi(uint32_t v) { return __uint_as_float(v & 0xFFFF0000u); }
__device__ __forceinline__ float bround(float v) { return blo(pack2(v, 0.f)); }
__device__ __forceinline__ uint32_t hadd2(uint32_t a, uint32_t b) { uint32_t r; asm("add.rn.bf16x2 %0, %1, %2;" : "=r"(r) : "r"(a), "r"(b)); return r; }
__device__ __forceinline__ uint32_t hmul2(uint32_t a, uint32_t b) { uint32_t r; asm("mul.rn.bf16x2 %0, %1, %2;" : "=r"(r) : "r"(a), "r"(b)); return r; }
__device__ __forceinline__ uint32_t prmt(uint32_t a, uint32_t b, uint32_t s) { uint32_t r; asm("prmt.b32 %0, %1, %2, %3;" : "=r"(r) : "r"(a), "r"(b), "r"(s)); return r; }
__device__ __forceinline__ float rcp(float v) { float r; asm("rcp.approx.ftz.f32 %0, %1;" : "=f"(r) : "f"(v)); return r; }
__device__ __forceinline__ float rsq(float v) { float r; asm("rsqrt.approx.ftz.f32 %0, %1;" : "=f"(r) : "f"(v)); return r; }
__device__ __forceinline__ float shx(float v, int m) { return __shfl_xor_sync(0xffffffffu, v, m); }
__device__ __forceinline__ float gelu_t(float v, float k0, float k1) {
    float t;
    asm("tanh.approx.f32 %0, %1;" : "=f"(t) : "f"(v * fmaf(v * v, k1, k0)));
    return t;
}
constexpr float GK0 = 0.7978845608028654f, GK1 = 0.0356774081363001f;
__device__ __forceinline__ uint32_t split2(float c) { const float h = bround(c); return pack2(c - h, h); }
template <int NV> __device__ __forceinline__ void halve(float* v, int mask, bool up) {
#pragma unroll
    for (int i = 0; i < NV / 2; i++) {
        float send = up ? v[i] : v[i + NV / 2], keep = up ? v[i + NV / 2] : v[i];
        v[i] = keep + shx(send, mask);
    }
}

struct cf { float x, y; };
__device__ __forceinline__ cf cmul(cf a, cf b) { cf r; r.x = fmaf(a.x, b.x, -a.y * b.y); r.y = fmaf(a.x, b.y, a.y * b.x); return r; }
__device__ __forceinline__ cf cexp2(float e, float th) {
    float m; asm("ex2.approx.ftz.f32 %0, %1;" : "=f"(m) : "f"(e));
    cf r; r.x = m * __cosf(th); r.y = m * __sinf(th); return r;
}

__device__ __forceinline__ void mma(float* d, uint32_t a0, uint32_t a1, uint32_t a2, uint32_t a3, uint32_t b0, uint32_t b1) {
    asm volatile("mma.sync.aligned.m16n8k16.row.col.f32.bf16.bf16.f32 {%0,%1,%2,%3},{%4,%5,%6,%7},{%8,%9},{%0,%1,%2,%3};"
                 : "+f"(d[0]), "+f"(d[1]), "+f"(d[2]), "+f"(d[3]) : "r"(a0), "r"(a1), "r"(a2), "r"(a3), "r"(b0), "r"(b1));
}
__device__ __forceinline__ void mmap(float* d, const uint32_t* a, const uint32_t* b) { mma(d, a[0], a[1], a[2], a[3], b[0], b[1]); }
__device__ __forceinline__ void mmar(float* d, const float* c, const uint32_t* a, const uint32_t* b) {
    asm volatile("mma.sync.aligned.m16n8k16.row.col.f32.bf16.bf16.f32 {%0,%1,%2,%3},{%4,%5,%6,%7},{%8,%9},{%10,%11,%12,%13};"
                 : "=f"(d[0]), "=f"(d[1]), "=f"(d[2]), "=f"(d[3])
                 : "r"(a[0]), "r"(a[1]), "r"(a[2]), "r"(a[3]), "r"(b[0]), "r"(b[1]), "f"(c[0]), "f"(c[1]), "f"(c[2]), "f"(c[3]));
}
__device__ __forceinline__ uint32_t cpy(uint32_t a, uint32_t z, int k) { return a + z * (uint32_t)k; }

#define WG_FENCE() asm volatile("wgmma.fence.sync.aligned;" ::: "memory")
#define WG_COMMIT() asm volatile("wgmma.commit_group.sync.aligned;" ::: "memory")
#define WG_WAIT(n) asm volatile("wgmma.wait_group.sync.aligned " #n ";" ::: "memory")
template <int N> __device__ __forceinline__ void pin(float* d) {
#pragma unroll
    for (int i = 0; i < N; i++) asm volatile("" : "+f"(d[i])::"memory");
}
template <int N> __device__ __forceinline__ void pinu(uint32_t* d) {
#pragma unroll
    for (int i = 0; i < N; i++) asm volatile("" : "+r"(d[i])::"memory");
}
constexpr uint32_t SMEM_BASE = 1024;
__device__ __forceinline__ uint32_t dlo(uint32_t off, uint32_t lbo) { return ((SMEM_BASE + off) >> 4) + ((lbo >> 4) << 16); }
template <int TA> __device__ __forceinline__ void wgmma_ss64(float* d, uint32_t da, uint32_t db, int sd) {
    asm volatile("{.reg .pred p; .reg .b64 a, b; setp.ne.b32 p, %34, 0; mov.b64 a, {%32, 0x40000040}; mov.b64 b, {%33, 0x40000040};\n"
                 "wgmma.mma_async.sync.aligned.m64n64k16.f32.bf16.bf16 {%0, %1, %2, %3, %4, %5, %6, %7, %8, %9, %10, %11, %12, %13, %14, %15, %16, %17, %18, %19, %20, %21, %22, %23, %24, %25, %26, %27, %28, %29, %30, %31}, a, b, p, 1, 1, %35, 1;}"
                 : "+f"(d[0]), "+f"(d[1]), "+f"(d[2]), "+f"(d[3]), "+f"(d[4]), "+f"(d[5]), "+f"(d[6]), "+f"(d[7]),
                   "+f"(d[8]), "+f"(d[9]), "+f"(d[10]), "+f"(d[11]), "+f"(d[12]), "+f"(d[13]), "+f"(d[14]), "+f"(d[15]),
                   "+f"(d[16]), "+f"(d[17]), "+f"(d[18]), "+f"(d[19]), "+f"(d[20]), "+f"(d[21]), "+f"(d[22]), "+f"(d[23]),
                   "+f"(d[24]), "+f"(d[25]), "+f"(d[26]), "+f"(d[27]), "+f"(d[28]), "+f"(d[29]), "+f"(d[30]), "+f"(d[31])
                 : "r"(da), "r"(db), "r"(sd), "n"(TA));
}
__device__ __forceinline__ void wgmma_ss224(float* d, uint32_t da, uint32_t db, int sd) {
    asm volatile("{.reg .pred p; .reg .b64 a, b; setp.ne.b32 p, %114, 0; mov.b64 a, {%112, 0x40000040}; mov.b64 b, {%113, 0x80000020};\n"
                 "wgmma.mma_async.sync.aligned.m64n224k16.f32.bf16.bf16 {%0, %1, %2, %3, %4, %5, %6, %7, %8, %9, %10, %11, %12, %13, %14, %15, %16, %17, %18, %19, %20, %21, %22, %23, %24, %25, %26, %27, %28, %29, %30, %31, %32, %33, %34, %35, %36, %37, %38, %39, %40, %41, %42, %43, %44, %45, %46, %47, %48, %49, %50, %51, %52, %53, %54, %55, %56, %57, %58, %59, %60, %61, %62, %63, %64, %65, %66, %67, %68, %69, %70, %71, %72, %73, %74, %75, %76, %77, %78, %79, %80, %81, %82, %83, %84, %85, %86, %87, %88, %89, %90, %91, %92, %93, %94, %95, %96, %97, %98, %99, %100, %101, %102, %103, %104, %105, %106, %107, %108, %109, %110, %111}, a, b, p, 1, 1, %115, 1;}"
                 : "+f"(d[0]), "+f"(d[1]), "+f"(d[2]), "+f"(d[3]), "+f"(d[4]), "+f"(d[5]), "+f"(d[6]), "+f"(d[7]),
                   "+f"(d[8]), "+f"(d[9]), "+f"(d[10]), "+f"(d[11]), "+f"(d[12]), "+f"(d[13]), "+f"(d[14]), "+f"(d[15]),
                   "+f"(d[16]), "+f"(d[17]), "+f"(d[18]), "+f"(d[19]), "+f"(d[20]), "+f"(d[21]), "+f"(d[22]), "+f"(d[23]),
                   "+f"(d[24]), "+f"(d[25]), "+f"(d[26]), "+f"(d[27]), "+f"(d[28]), "+f"(d[29]), "+f"(d[30]), "+f"(d[31]),
                   "+f"(d[32]), "+f"(d[33]), "+f"(d[34]), "+f"(d[35]), "+f"(d[36]), "+f"(d[37]), "+f"(d[38]), "+f"(d[39]),
                   "+f"(d[40]), "+f"(d[41]), "+f"(d[42]), "+f"(d[43]), "+f"(d[44]), "+f"(d[45]), "+f"(d[46]), "+f"(d[47]),
                   "+f"(d[48]), "+f"(d[49]), "+f"(d[50]), "+f"(d[51]), "+f"(d[52]), "+f"(d[53]), "+f"(d[54]), "+f"(d[55]),
                   "+f"(d[56]), "+f"(d[57]), "+f"(d[58]), "+f"(d[59]), "+f"(d[60]), "+f"(d[61]), "+f"(d[62]), "+f"(d[63]),
                   "+f"(d[64]), "+f"(d[65]), "+f"(d[66]), "+f"(d[67]), "+f"(d[68]), "+f"(d[69]), "+f"(d[70]), "+f"(d[71]),
                   "+f"(d[72]), "+f"(d[73]), "+f"(d[74]), "+f"(d[75]), "+f"(d[76]), "+f"(d[77]), "+f"(d[78]), "+f"(d[79]),
                   "+f"(d[80]), "+f"(d[81]), "+f"(d[82]), "+f"(d[83]), "+f"(d[84]), "+f"(d[85]), "+f"(d[86]), "+f"(d[87]),
                   "+f"(d[88]), "+f"(d[89]), "+f"(d[90]), "+f"(d[91]), "+f"(d[92]), "+f"(d[93]), "+f"(d[94]), "+f"(d[95]),
                   "+f"(d[96]), "+f"(d[97]), "+f"(d[98]), "+f"(d[99]), "+f"(d[100]), "+f"(d[101]), "+f"(d[102]), "+f"(d[103]),
                   "+f"(d[104]), "+f"(d[105]), "+f"(d[106]), "+f"(d[107]), "+f"(d[108]), "+f"(d[109]), "+f"(d[110]), "+f"(d[111])
                 : "r"(da), "r"(db), "r"(sd), "n"(0));
}
template <int TB> __device__ __forceinline__ void wgmma_rs64(float* d, uint32_t a0, uint32_t a1, uint32_t a2, uint32_t a3, uint32_t db, int sd) {
    asm volatile("{.reg .pred p; .reg .b64 b; setp.ne.b32 p, %37, 0; mov.b64 b, {%36, %39};\n"
                 "wgmma.mma_async.sync.aligned.m64n64k16.f32.bf16.bf16 {%0, %1, %2, %3, %4, %5, %6, %7, %8, %9, %10, %11, %12, %13, %14, %15, %16, %17, %18, %19, %20, %21, %22, %23, %24, %25, %26, %27, %28, %29, %30, %31}, {%32, %33, %34, %35}, b, p, 1, 1, %38;}"
                 : "+f"(d[0]), "+f"(d[1]), "+f"(d[2]), "+f"(d[3]), "+f"(d[4]), "+f"(d[5]), "+f"(d[6]), "+f"(d[7]),
                   "+f"(d[8]), "+f"(d[9]), "+f"(d[10]), "+f"(d[11]), "+f"(d[12]), "+f"(d[13]), "+f"(d[14]), "+f"(d[15]),
                   "+f"(d[16]), "+f"(d[17]), "+f"(d[18]), "+f"(d[19]), "+f"(d[20]), "+f"(d[21]), "+f"(d[22]), "+f"(d[23]),
                   "+f"(d[24]), "+f"(d[25]), "+f"(d[26]), "+f"(d[27]), "+f"(d[28]), "+f"(d[29]), "+f"(d[30]), "+f"(d[31])
                 : "r"(a0), "r"(a1), "r"(a2), "r"(a3), "r"(db), "r"(sd), "n"(TB), "n"(TB ? 0x40000040 : 8));
}
__device__ __forceinline__ void wgmma_rs224(float* d, uint32_t a0, uint32_t a1, uint32_t a2, uint32_t a3, uint32_t db, int sd) {
    asm volatile("{.reg .pred p; .reg .b64 b; setp.ne.b32 p, %117, 0; mov.b64 b, {%116, %119};\n"
                 "wgmma.mma_async.sync.aligned.m64n224k16.f32.bf16.bf16 {%0, %1, %2, %3, %4, %5, %6, %7, %8, %9, %10, %11, %12, %13, %14, %15, %16, %17, %18, %19, %20, %21, %22, %23, %24, %25, %26, %27, %28, %29, %30, %31, %32, %33, %34, %35, %36, %37, %38, %39, %40, %41, %42, %43, %44, %45, %46, %47, %48, %49, %50, %51, %52, %53, %54, %55, %56, %57, %58, %59, %60, %61, %62, %63, %64, %65, %66, %67, %68, %69, %70, %71, %72, %73, %74, %75, %76, %77, %78, %79, %80, %81, %82, %83, %84, %85, %86, %87, %88, %89, %90, %91, %92, %93, %94, %95, %96, %97, %98, %99, %100, %101, %102, %103, %104, %105, %106, %107, %108, %109, %110, %111}, {%112, %113, %114, %115}, b, p, 1, 1, %118;}"
                 : "+f"(d[0]), "+f"(d[1]), "+f"(d[2]), "+f"(d[3]), "+f"(d[4]), "+f"(d[5]), "+f"(d[6]), "+f"(d[7]),
                   "+f"(d[8]), "+f"(d[9]), "+f"(d[10]), "+f"(d[11]), "+f"(d[12]), "+f"(d[13]), "+f"(d[14]), "+f"(d[15]),
                   "+f"(d[16]), "+f"(d[17]), "+f"(d[18]), "+f"(d[19]), "+f"(d[20]), "+f"(d[21]), "+f"(d[22]), "+f"(d[23]),
                   "+f"(d[24]), "+f"(d[25]), "+f"(d[26]), "+f"(d[27]), "+f"(d[28]), "+f"(d[29]), "+f"(d[30]), "+f"(d[31]),
                   "+f"(d[32]), "+f"(d[33]), "+f"(d[34]), "+f"(d[35]), "+f"(d[36]), "+f"(d[37]), "+f"(d[38]), "+f"(d[39]),
                   "+f"(d[40]), "+f"(d[41]), "+f"(d[42]), "+f"(d[43]), "+f"(d[44]), "+f"(d[45]), "+f"(d[46]), "+f"(d[47]),
                   "+f"(d[48]), "+f"(d[49]), "+f"(d[50]), "+f"(d[51]), "+f"(d[52]), "+f"(d[53]), "+f"(d[54]), "+f"(d[55]),
                   "+f"(d[56]), "+f"(d[57]), "+f"(d[58]), "+f"(d[59]), "+f"(d[60]), "+f"(d[61]), "+f"(d[62]), "+f"(d[63]),
                   "+f"(d[64]), "+f"(d[65]), "+f"(d[66]), "+f"(d[67]), "+f"(d[68]), "+f"(d[69]), "+f"(d[70]), "+f"(d[71]),
                   "+f"(d[72]), "+f"(d[73]), "+f"(d[74]), "+f"(d[75]), "+f"(d[76]), "+f"(d[77]), "+f"(d[78]), "+f"(d[79]),
                   "+f"(d[80]), "+f"(d[81]), "+f"(d[82]), "+f"(d[83]), "+f"(d[84]), "+f"(d[85]), "+f"(d[86]), "+f"(d[87]),
                   "+f"(d[88]), "+f"(d[89]), "+f"(d[90]), "+f"(d[91]), "+f"(d[92]), "+f"(d[93]), "+f"(d[94]), "+f"(d[95]),
                   "+f"(d[96]), "+f"(d[97]), "+f"(d[98]), "+f"(d[99]), "+f"(d[100]), "+f"(d[101]), "+f"(d[102]), "+f"(d[103]),
                   "+f"(d[104]), "+f"(d[105]), "+f"(d[106]), "+f"(d[107]), "+f"(d[108]), "+f"(d[109]), "+f"(d[110]), "+f"(d[111])
                 : "r"(a0), "r"(a1), "r"(a2), "r"(a3), "r"(db), "r"(sd), "n"(0), "n"(0 ? 0x40000040 : 8));
}


__device__ __forceinline__ uint32_t vecpos(int kw) { return (kw >> 4) * 64 + (kw & 3) * 16 + ((kw >> 2) & 1) * 8 + ((kw >> 3) & 1) * 4; }

__device__ __forceinline__ uint32_t wstage(int q) { return (q & 1) * 28672 + (q & 2) * 32768; }

__global__ void __launch_bounds__(384, 1)
fused_kernel(const Params P, const __grid_constant__ Maps M)
{
    extern __shared__ __align__(1024) uint8_t smem_raw[];
    const uint32_t sb = __shfl_sync(0xffffffffu, (uint32_t)__cvta_generic_to_shared(smem_raw), 0);
    const int tid = threadIdx.x, lane = tid & 31, warp = __shfl_sync(0xffffffffu, tid >> 5, 0), g = lane >> 2, q = lane & 3;
    const int cl = blockIdx.x >> 1, pr = blockIdx.x & 1;
    int gi, pa;
    if (cl < 4) { gi = 15; pa = cl; } else if (cl < 36) { gi = (cl - 4) & 7; pa = (cl - 4) >> 3; } else { gi = 8 + (cl - 36) % 7; pa = (cl - 36) / 7; }
    const int fs = 2 * pa + pr;
    const int cs = 4 * pr + pa;
    const int b = 8 * gi + fs;
    const uint32_t bar0 = sb + SM_BAR;
#define BAR(i) (bar0 + 8 * (i))

    if (warp < 8) {
        const int s = warp >> 2, w4 = warp & 3, wt = tid & 127;
        const size_t po = (size_t)b * 512 + 2 * tid;
        const uint32_t pAre = ldg32(P.Are + po), pAim = ldg32(P.Aim + po), pBre = ldg32(P.Bre + po), pBim = ldg32(P.Bim + po),
                       pCre = ldg32(P.Cre + po), pCim = ldg32(P.Cim + po);
        const float ldt = __bfloat162float(P.logdt[4 * b + (tid >> 6)]);
        const float dsk = __bfloat162float(P.dskip[4 * b + (tid >> 6)]);
        const uint32_t ep = ldr32(&G.epoch[b]) + 1;
        asm volatile("barrier.cluster.arrive.relaxed.aligned;" ::: "memory");
        asm volatile("setmaxnreg.inc.sync.aligned.u32 224;");
        for (int i = tid; i < 4 * WD_B / 16; i += 256) sts128(sb + SM_WD + i * 16, make_uint4(0, 0, 0, 0));
        if (tid < 152) sts128(sb + SM_UW + (tid / 38) * UW_B + (tid % 38) * 16, make_uint4(0, 0, 0, 0));
        {
            const int mh = warp & 1;
            const uint32_t pt = sb + SM_W1 + warp * PT_B;
            {
                const float dt = bround(expf(ldt));
                cf z[2], w[2], r0[2], r2[2], r4[2], t[2];
#pragma unroll
                for (int m = 0; m < 2; m++) {
                    const float a = dt * (m ? bhi(pAre) : blo(pAre)) * 1.4426950408889634f, th = dt * (m ? bhi(pAim) : blo(pAim));
                    const cf z64 = cexp2(64.f * a, 64.f * th);
                    sts128(pt + 24 * PT_PITCH + lane * 32 + m * 16, make_uint4(__float_as_uint(8.f * a), __float_as_uint(8.f * th), __float_as_uint(z64.x), __float_as_uint(z64.y)));
                    z[m] = cexp2(a, -th); w[m] = cexp2(256.f * a, -256.f * th);
                    cf C, B;
                    C.x = m ? bhi(pCre) : blo(pCre); C.y = -(m ? bhi(pCim) : blo(pCim));
                    B.x = dt * (m ? bhi(pBre) : blo(pBre)); B.y = -dt * (m ? bhi(pBim) : blo(pBim));
                    r0[m] = cmul(C, B);
                }
                const uint32_t pp = pt + lane * 8;
#define PST(j, v) sts64(pp + (j) * PT_PITCH, pack2(v[0].x, v[0].y), pack2(v[1].x, v[1].y))
#define CM(d, a, c) d[0] = cmul(a[0], c[0]); d[1] = cmul(a[1], c[1])
                PST(0, r0); CM(t, r0, z); PST(1, t); CM(r2, t, z); PST(2, r2); CM(t, r2, z); PST(3, t); CM(r4, t, z); PST(4, r4);
                CM(r2, r2, w); PST(9, r2); CM(t, r4, z); PST(5, t); CM(r2, t, z); PST(6, r2); CM(t, r2, z); PST(7, t); CM(r2, r2, w); PST(11, r2);
                CM(r0, r0, w); PST(8, r0); CM(r4, r4, w); PST(10, r4); CM(r0, r0, w); PST(12, r0); CM(r4, r4, w); PST(13, r4);
                CM(r0, r0, w); PST(14, r0); CM(r4, r4, w); PST(15, r4);
#pragma unroll 1
                for (int j = 16; j < 21; j++) { CM(r0, r0, w); PST(j, r0); }
#undef PST
#undef CM
            }
            __syncwarp();
            float KA[2][3][4];
#pragma unroll
            for (int n = 0; n < 24; n++) (&KA[0][0][0])[n] = 0.f;
            const uint32_t ba = pt + (lane & 7) * PT_PITCH + (lane >> 3) * 16, pa_ = pt + 24 * PT_PITCH + q * 16;
            const float gf = (float)g;
#pragma unroll 1
            for (int k = 0; k < 4; k++) {
                uint32_t bb[3][4];
#pragma unroll
                for (int n = 0; n < 3; n++) ldsm4(bb[n], ba + n * 8 * PT_PITCH + k * 64);
#pragma unroll
                for (int h = 0; h < 2; h++) {
                    uint32_t a[2][4];
#pragma unroll
                    for (int m = 0; m < 2; m++) {
                        const uint4 pv = lds128(pa_ + k * 256 + h * 128 + m * 64);
                        cf e = cexp2(gf * __uint_as_float(pv.x), gf * __uint_as_float(pv.y)), z64;
                        z64.x = __uint_as_float(pv.z); z64.y = __uint_as_float(pv.w);
                        a[0][2 * m] = pack2(e.x, e.y); e = cmul(e, z64); a[0][2 * m + 1] = pack2(e.x, e.y); e = cmul(e, z64);
                        a[1][2 * m] = pack2(e.x, e.y); e = cmul(e, z64); a[1][2 * m + 1] = pack2(e.x, e.y);
                    }
#pragma unroll
                    for (int n = 0; n < 3; n++) { mmap(KA[0][n], a[0], bb[n] + 2 * h); mmap(KA[1][n], a[1], bb[n] + 2 * h); }
                }
            }
            float KG[3][4];
            __syncwarp();
#pragma unroll
            for (int n = 0; n < 3; n++) {
                sts128(pt + n * 512 + lane * 16, mh ? make_uint4(__float_as_uint(KA[0][n][0]), __float_as_uint(KA[0][n][1]), __float_as_uint(KA[0][n][2]), __float_as_uint(KA[0][n][3]))
                                                    : make_uint4(__float_as_uint(KA[1][n][0]), __float_as_uint(KA[1][n][1]), __float_as_uint(KA[1][n][2]), __float_as_uint(KA[1][n][3])));
            }
            bar_sync(1, 256);
#pragma unroll
            for (int n = 0; n < 3; n++) {
                const uint4 v = lds128(sb + SM_W1 + (warp ^ 1) * PT_B + n * 512 + lane * 16);
                KG[n][0] = __uint_as_float(v.x) + (mh ? KA[1][n][0] : KA[0][n][0]); KG[n][1] = __uint_as_float(v.y) + (mh ? KA[1][n][1] : KA[0][n][1]);
                KG[n][2] = __uint_as_float(v.z) + (mh ? KA[1][n][2] : KA[0][n][2]); KG[n][3] = __uint_as_float(v.w) + (mh ? KA[1][n][3] : KA[0][n][3]);
            }
            if (mh == 0 && lane == 0) KG[0][0] += dsk;
            constexpr uint64_t CB[3][2] = {
                {(uint64_t)T0o | ((uint64_t)T2o << 16) | ((uint64_t)T4o << 32) | ((uint64_t)(TM2o + 1) << 48),
                 (uint64_t)T1o | ((uint64_t)T3o << 16) | ((uint64_t)T5o << 32) | ((uint64_t)(TM1o + 1) << 48)},
                {(uint64_t)(T0o + 32) | ((uint64_t)(T4o + 32) << 16) | ((uint64_t)(T0o + 64) << 32) | ((uint64_t)(T0o + 96) << 48),
                 (uint64_t)(T2o + 32) | ((uint64_t)(TM2o + 33) << 16) | ((uint64_t)(T4o + 64) << 32) | ((uint64_t)(T4o + 96) << 48)},
                {(uint64_t)(T0o + 128) | ((uint64_t)(T0o + 192) << 16) | ((uint64_t)(T0o + 256) << 32),
                 (uint64_t)(T0o + 160) | ((uint64_t)(T0o + 224) << 16)}};
            const uint32_t wd = sb + SM_WD + (warp >> 1) * WD_B + (16 * mh + g) * 4;
#pragma unroll
            for (int n = 0; n < 3; n++)
#pragma unroll
                for (int e = 0; e < 2; e++) {
                    const uint32_t a = wd + 4 * (uint32_t)((CB[n][e] >> (16 * q)) & 0xFFFF);
                    const uint32_t v = pack2(KG[n][e], KG[n][2 + e]);
                    const bool ok0 = n < 2 || q < 2 || (e == 0 && q == 2 && mh == 0), ok1 = n < 2 || q < 2;
                    if (ok0) { sts16(a, v); sts16(a + 6, v); }
                    if (ok1) { sts16(a + 32, v >> 16); sts16(a + 38, v >> 16); }
                }
        }
        bar_sync(5, 384);
        {
            const int ua = tid >> 3, rho = tid & 7;
            const uint2* stp = G.stats0 + 32 * ua + rho;
            uint2 st[10];
#define STI(i) (((i) / 5) * 1024 + ((i) % 5) * 8 - ((i) == 9 && ua == 31 ? 8 : 0))
#pragma unroll
            for (int i = 0; i < 10; i++) st[i] = ldr64(stp + STI(i));
            uint32_t A[32][4];
            {
                const int o = g - 2 * q;
                const uint32_t wd = sb + SM_WD + w4 * WD_B + 4 * o;
                const uint32_t sel0 = (o >= 0 ? 0x54u : 0x10u) | (o >= 1 ? 0x7600u : 0x3200u);
                const uint32_t oz = lds32(sb + SM_WD);
#define LT(T, h) lds32(wd + 4 * ((T) + 8 * (h)))
#define QUAD(Q, a0, a1, a2, a3, id) { Q[0] = a0; Q[1] = a1; Q[2] = cpy(a2, oz, 2 * (id) + 3); Q[3] = cpy(a3, oz, 2 * (id) + 4); }
#define QF(Q, X, L, id) QUAD(Q, X[2 * (L)], X[2 * (L) + 1], (L) ? X[(L) ? 2 * (L) - 1 : 0] : 0u, X[2 * (L)], id)
#define AN(e, L) A[3 * (e) + (L)]
#define AM(e, L) A[24 + 2 * (e) + (L) - 3]
#define A0(a) A[a]
#define A4(a) A[11 + (a)]
                if (s) {
                    const uint32_t sel1 = (o >= 1 ? 0x54u : 0x10u) | (o >= 2 ? 0x7600u : 0x3200u);
                    uint32_t T0[10], T4[10], X[10];
#pragma unroll
                    for (int h = 0; h < 10; h++) { T0[h] = LT(T0o, h); T4[h] = LT(T4o, h); }
#pragma unroll
                    for (int L = 0; L < 3; L++) { QF(AN(2, L), T0, L, 0) QF(AN(6, L), T4, L, 1) }
#pragma unroll
                    for (int L = 3; L < 5; L++) { QF(AM(1, L), T0, L, 0) QF(AM(3, L), T4, L, 1) }
#pragma unroll
                    for (int k = 0; k < 2; k++) {
#pragma unroll
                        for (int h = 0; h < 9; h++) X[h] = LT(k ? T2o : TM2o, h);
                        X[8] = prmt(X[8], T0[8], k ? sel0 : sel1); X[9] = cpy(T0[9], oz, 31 + k);
#pragma unroll
                        for (int L = 0; L < 3; L++) QF(AN(4 * k, L), X, L, 2 + k)
#pragma unroll
                        for (int L = 3; L < 5; L++) QF(AM(2 * k, L), X, L, 2 + k)
                    }
#pragma unroll
                    for (int k = 0; k < 4; k++) {
#pragma unroll
                        for (int h = 0; h < 5; h++) X[h] = LT(k == 0 ? TM1o : k == 1 ? T1o : k == 2 ? T3o : T5o, h);
                        X[4] = prmt(X[4], k < 2 ? T0[4] : T4[4], k ? sel0 : sel1); X[5] = cpy(k < 2 ? T0[5] : T4[5], oz, 33 + k);
#pragma unroll
                        for (int L = 0; L < 3; L++) QF(AN(2 * k + 1, L), X, L, 4 + k)
                    }
                } else {
                    const uint32_t selp = (g & 1) ? 0x7610u : 0x1010u;
                    uint32_t T0[33], T4[32];
#pragma unroll
                    for (int h = 9; h < 33; h++) T0[h] = LT(T0o, h);
#pragma unroll
                    for (int h = 9; h < 17; h++) T4[h] = LT(T4o, h);
                    const uint32_t T3x = prmt(T4[16], T0[16], sel0), T5x = prmt(T4[16], LT(T0o + 1, 16), sel0), T5y = LT(T0o + 1, 17);
                    QUAD(A[22], T3x, cpy(T0[17], oz, 31), T4[15], T3x, 2)
                    QUAD(A[23], q ? T5x : (T5x & 0xFFFF0000u), q ? T5y : (T5y & 0xFFFF0000u), T4[15], T5x, 3)
#pragma unroll
                    for (int h = 16; h < 32; h++) {
                        const uint32_t v = prmt(lds32(wd + 4 * (g & 1) + 4 * (T0o + 8 * h)), T0[h], selp);
                        T4[h] = h == 16 ? prmt(T4[16], v, sel0) : v;
                    }
                    QUAD(A[24], 0u, 0u, T0[31], q == 3 ? (T0[32] & 0xFFFF0000u) : 0u, 4)
#pragma unroll
                    for (int L = 5; L < 16; L++) { QF(A0(L - 5), T0, L, 0) QF(A4(L - 5), T4, L, 1) }
                }
#undef LT
#undef QUAD
#undef QF
            }
            {
                for (int it = 0;; it++) {
                    uint32_t bad = 0;
#pragma unroll
                    for (int i = 0; i < 10; i++) bad |= stale2(st[i], ep);
                    if (!any(bad)) break;
                    if (it > SPIN_MAX) __trap();
#pragma unroll
                    for (int i = 0; i < 10; i++) st[i] = ldr64(stp + STI(i));
                }
#undef STI
                mbar_wait(BAR(B_MOD));
                const uint4 sa4 = lds128(sb + SM_OWN), ca4 = lds128(sb + SM_OWN + 16);
                const float sa[4] = {__uint_as_float(sa4.x), __uint_as_float(sa4.y), __uint_as_float(sa4.z), __uint_as_float(sa4.w)};
                const float ca[4] = {__uint_as_float(ca4.x), __uint_as_float(ca4.y), __uint_as_float(ca4.z), __uint_as_float(ca4.w)};
                const uint32_t pad = rho >= 3 ? 32 : 0;
                mbar_wait(BAR(B_XC));
#pragma unroll 1
                for (int a = ua; a < 64; a += 32) {
                    const uint32_t ub = sb + SM_UW + 4 * (40 * (a + 4) + rho + 5), xb = sb + SM_XS + 4 * (40 * a + rho);
                    const uint32_t xs = sb + SM_XC + (32 * a + rho) * 16 + 8 * pr;
                    float hp[4];
                    if (a >= 28) mbar_wait(BAR(B_XC + 1));
#pragma unroll
                    for (int i = 0; i < 5; i++) {
                        const uint2 xc = lds64(xs + 128 * i);
                        const float r = __uint_as_float(st[i].x), c = __uint_as_float(st[i].y);
                        st[i] = st[5 + i];
                        float h[4];
                        h[0] = fmaf(fmaf(blo(xc.x), r, c), ca[0], sa[0]); h[1] = fmaf(fmaf(bhi(xc.x), r, c), ca[1], sa[1]);
                        h[2] = fmaf(fmaf(blo(xc.y), r, c), ca[2], sa[2]); h[3] = fmaf(fmaf(bhi(xc.y), r, c), ca[3], sa[3]);
                        if (i == 4 && a == 63) h[0] = h[1] = h[2] = h[3] = 0.f;
                        if (i < 4) { sts32(xb + 32 * i, xc.x); sts32(xb + XS_B + 32 * i, xc.y); }
#pragma unroll
                        for (int c = 0; c < 4; c++) {
                            if (i) sts32(ub + c * UW_B + 32 * (i - 1) + (i == 4 ? pad : 0), pack2(hp[c], h[c]));
                            else if (a == 0) sts32(ub + c * UW_B - 64 + pad, pack2(0.f, h[c]));
                            hp[c] = h[c];
                        }
                    }
                }
            }
            bar_sync(1, 256);
            if (tid == 0) {
                fence_async_smem();
                tma2d(sb + SM_W1, &M.m[tmW1], 64 * cs, 0, BAR(B_W1FULL));
                tma2d(sb + SM_W1 + 32768, &M.m[tmW1], 64 * cs, 256, BAR(B_W1FULL));
            }
            uint32_t ub = sb + SM_UW + w4 * UW_B + 4 * (16 * q + 8 * (q >> 1) + g);
            uint32_t dep = sb + SM_DEP + w4 * 512 + lane * 16;
            const float zero4[4] = {0.f, 0.f, 0.f, 0.f};
            uint32_t f[9][2];
#define LF(k) { f[k][0] = lds32(ub + (8 - (k)) * 4); f[k][1] = lds32(ub + 320 + (8 - (k)) * 4); }
#define SUM3(d, a, c, e) { d[0] = hadd2(hadd2(f[a][0], f[c][0]), f[e][0]); d[1] = hadd2(hadd2(f[a][1], f[c][1]), f[e][1]); }
#define SUMX(d, p, a, c) { d[0] = hadd2(p[0], hadd2(f[a][0], f[c][0])); d[1] = hadd2(p[1], hadd2(f[a][1], f[c][1])); }
            if (s) {
                float Pa[5][4], Ra[3][4];
                uint32_t u3[2];
                LF(1) LF(2)
                mmar(Pa[1], zero4, AN(0, 1), f[1]); mmar(Pa[2], zero4, AN(0, 2), f[1]);
                mmar(Pa[3], zero4, AM(0, 3), f[1]); mmar(Pa[4], zero4, AM(0, 4), f[1]);
                mmar(Ra[1], zero4, AN(1, 1), f[2]); mmar(Ra[2], zero4, AN(1, 2), f[2]);
                mmap(Pa[3], AM(1, 3), f[2]); mmap(Pa[4], AM(1, 4), f[2]);
                ub += 640;
                LF(1) LF(2) LF(3) LF(4) LF(5) LF(6) LF(7) LF(8)
#pragma unroll 1
                for (int lim = 15; lim >= 2; lim--) {
                    ub += 640;
                    SUM3(u3, 2, 4, 3)
                    mmar(Pa[0], Pa[1], AN(0, 0), f[1]); mmar(Pa[1], Pa[2], AN(0, 1), f[1]); mmar(Pa[2], Pa[3], AN(0, 2), f[1]);
                    mmar(Pa[3], Pa[4], AM(0, 3), f[1]); mmar(Pa[4], zero4, AM(0, 4), f[1]); LF(1)
                    mmar(Ra[0], Ra[1], AN(1, 0), f[2]); mmar(Ra[1], Ra[2], AN(1, 1), f[2]); mmar(Ra[2], zero4, AN(1, 2), f[2]); LF(2)
                    mmap(Pa[0], AN(2, 0), f[3]); mmap(Pa[1], AN(2, 1), f[3]); mmap(Pa[2], AN(2, 2), f[3]); LF(3)
                    mmap(Pa[3], AM(1, 3), u3); mmap(Pa[4], AM(1, 4), u3);
                    SUM3(u3, 6, 8, 7)
                    mmap(Ra[0], AN(3, 0), f[4]); mmap(Ra[1], AN(3, 1), f[4]); mmap(Ra[2], AN(3, 2), f[4]); LF(4)
                    mmap(Pa[0], AN(4, 0), f[5]); mmap(Pa[1], AN(4, 1), f[5]); mmap(Pa[2], AN(4, 2), f[5]);
                    mmap(Ra[0], AN(5, 0), f[6]);
                    mmap(Pa[3], AM(2, 3), f[5]); mmap(Pa[4], AM(2, 4), f[5]); LF(5)
                    mmap(Pa[0], AN(6, 0), f[7]); mmap(Ra[1], AN(5, 1), f[6]);
                    mmap(Ra[0], AN(7, 0), f[8]); mmap(Ra[2], AN(5, 2), f[6]); LF(6)
                    mmap(Pa[1], AN(6, 1), f[7]); mmap(Pa[2], AN(6, 2), f[7]); LF(7)
                    mmap(Pa[3], AM(3, 3), u3); mmap(Pa[4], AM(3, 4), u3);
                    mmap(Ra[1], AN(7, 1), f[8]); mmap(Ra[2], AN(7, 2), f[8]); LF(8)
                    sts128(dep, make_uint4(__float_as_uint(Pa[0][0] + Ra[0][0]), __float_as_uint(Pa[0][1] + Ra[0][1]),
                                           __float_as_uint(Pa[0][2] + Ra[0][2]), __float_as_uint(Pa[0][3] + Ra[0][3])));
                    dep += 2048;
                    warp_arrive(BAR(B_NEAR + 15 - lim));
                }
#pragma unroll 1
                for (int lim = 1; lim >= 0; lim--) {
                    ub += 640;
                    mmar(Pa[0], Pa[1], AN(0, 0), f[1]); mmar(Ra[0], Ra[1], AN(1, 0), f[2]); mmar(Pa[1], Pa[2], AN(0, 1), f[1]); mmar(Ra[1], Ra[2], AN(1, 1), f[2]); LF(1) LF(2)
                    mmap(Pa[0], AN(2, 0), f[3]); mmap(Ra[0], AN(3, 0), f[4]); mmap(Pa[1], AN(2, 1), f[3]); mmap(Ra[1], AN(3, 1), f[4]); LF(3) LF(4)
                    mmap(Pa[0], AN(4, 0), f[5]); mmap(Ra[0], AN(5, 0), f[6]); mmap(Pa[1], AN(4, 1), f[5]); mmap(Ra[1], AN(5, 1), f[6]); LF(5) LF(6)
                    mmap(Pa[0], AN(6, 0), f[7]); mmap(Ra[0], AN(7, 0), f[8]); mmap(Pa[1], AN(6, 1), f[7]); mmap(Ra[1], AN(7, 1), f[8]); LF(7) LF(8)
                    sts128(dep, make_uint4(__float_as_uint(Pa[0][0] + Ra[0][0]), __float_as_uint(Pa[0][1] + Ra[0][1]),
                                           __float_as_uint(Pa[0][2] + Ra[0][2]), __float_as_uint(Pa[0][3] + Ra[0][3])));
                    dep += 2048;
                    warp_arrive(BAR(B_NEAR + 15 - lim));
                }
                mbar_wait(BAR(B_W1RDY));
#pragma unroll 1
                for (int k = wt; k < 512; k += 128) {
                    const uint32_t c1 = lds32(sb + SM_CS + k * 8), c2 = prmt(c1, c1, 0x3232u), ra = sb + SM_W1 + k * 128;
                    uint4 w[8];
#pragma unroll
                    for (int j = 0; j < 8; j++) w[j] = lds128(ra + ((j ^ (k & 7)) << 4));
#pragma unroll
                    for (int j = 0; j < 8; j++) sts128(ra + ((j ^ (k & 7)) << 4), make_uint4(hmul2(w[j].x, c2), hmul2(w[j].y, c2), hmul2(w[j].z, c2), hmul2(w[j].w, c2)));
                }
                fence_async_smem();
                warp_arrive(BAR(B_W1SC));
            } else {
                float Fa[12][4], Fx[4] = {0.f, 0.f, 0.f, 0.f};
                uint32_t u3[2], u5[2], u7[2];
                LF(0) LF(1) LF(2)
                u5[0] = hadd2(f[1][0], f[2][0]); u5[1] = hadd2(f[1][1], f[2][1]); u7[0] = hadd2(u5[0], f[0][0]); u7[1] = hadd2(u5[1], f[0][1]);
#pragma unroll
                for (int a = 0; a < 11; a++) mmar(Fa[a], zero4, A0(a), a < 4 ? u5 : u7);
                mmar(Fa[11], zero4, A[24], u7);
                ub += 640;
                LF(0) LF(1) LF(2) LF(3) LF(4) LF(5) LF(6) LF(7) LF(8)
                uint32_t xa = sb + SM_XS + (w4 >> 1) * XS_B + 4 * (8 * g + 2 * q + 8 * (g >> 2));
                bf16* xo = G.x2t + (size_t)(4 * b + w4) * 2048 + 8 * g + 2 * q;
                const uint32_t xsel = (w4 & 1) ? 0x3244u : 0x1044u;
                mbar_wait(BAR(B_MOD + 1));
                const float ga = ldsf(sb + SM_OWN + 32 + 4 * w4);
#pragma unroll 1
                for (int lim = 14; lim >= -1; lim--) {
                    const uint2 x0 = lds64(xa), x1 = lds64(xa + 320);
                    mbar_wait(BAR(B_NEAR + 14 - lim));
                    const uint4 nv = lds128(dep);
                    float y[4] = {0.f, 0.f, 0.f, 0.f};
                    if (lim <= 10) {
                        y[0] = Fa[0][0]; y[1] = Fa[0][1]; y[2] = Fa[0][2]; y[3] = Fa[0][3];
                        if (lim >= 0) {
                            ub += 640;
                            SUM3(u3, 6, 8, 7) SUM3(u5, 2, 4, 3) SUMX(u5, u5, 1, 5) SUMX(u7, u5, 0, 6)
                            LF(0) LF(1) LF(2) LF(3) LF(4) LF(5)
                            mmar(Fa[0], Fa[1], A4(0), u3); mmar(Fa[1], Fa[2], A4(1), u3); mmar(Fa[2], Fa[3], A4(2), u3);
                            if (lim >= 3) {
                                mmar(Fa[3], Fa[4], A[22], f[6]); mmar(Fx, zero4, A[23], f[8]); mmar(Fa[4], Fa[5], A4(4), f[7]);
                                mmap(Fa[0], A0(0), u5); mmap(Fa[1], A0(1), u5); mmap(Fa[2], A0(2), u5);
                                if (lim >= 5) {
                                    mmar(Fa[5], Fa[6], A4(5), f[7]); mmar(Fa[6], Fa[7], A4(6), f[7]);
                                    if (lim >= 7) {
                                        mmar(Fa[7], Fa[8], A4(7), f[7]); mmar(Fa[8], Fa[9], A4(8), f[7]);
                                        mmar(Fa[9], Fa[10], A4(9), f[7]); mmar(Fa[10], Fa[11], A4(10), f[7]);
                                        mmap(Fa[7], A0(7), u7); mmap(Fa[8], A0(8), u7); mmap(Fa[9], A0(9), u7); mmap(Fa[10], A0(10), u7);
                                    }
                                    mmap(Fa[5], A0(5), u7); mmap(Fa[6], A0(6), u7);
                                }
                                mmap(Fa[3], A4(3), f[7]); mmap(Fx, A0(3), u5); mmap(Fa[4], A0(4), u7);
                            } else { mmap(Fa[0], A0(0), u5); mmap(Fa[1], A0(1), u5); mmap(Fa[2], A0(2), u5); }
                            LF(6) LF(7) LF(8)
                        }
                    }
                    stg32(xo, pack2(fmaf(ga, y[0] + __uint_as_float(nv.x), __uint_as_float(prmt(x0.x, 0, xsel))),
                                    fmaf(ga, y[1] + __uint_as_float(nv.y), __uint_as_float(prmt(x0.y, 0, xsel)))));
                    stg32(xo + 64, pack2(fmaf(ga, y[2] + __uint_as_float(nv.z), __uint_as_float(prmt(x1.x, 0, xsel))),
                                         fmaf(ga, y[3] + __uint_as_float(nv.w), __uint_as_float(prmt(x1.y, 0, xsel)))));
                    xa += 640; xo += 128; dep += 2048;
                    if (lim == 6) { warp_arrive(BAR(B_CONV)); }
                    Fa[3][0] += Fx[0]; Fa[3][1] += Fx[1]; Fa[3][2] += Fx[2]; Fa[3][3] += Fx[3];
                }
                warp_arrive(BAR(B_CONV + 1));
            }
#undef LF
#undef SUM3
#undef SUMX
#undef AN
#undef AM
#undef A0
#undef A4
        }

        const int tau = 16 * s + gi, row0 = 64 * tau + 16 * w4 + g;
        float acc[32];
        uint32_t x2p[16];
        {
            float mo[24];
#pragma unroll
            for (int i = 0; i < 24; i++) mo[i] = 0.f;
            const int srow = wt >> 1;
            const uint32_t soff = srow * 128 + ((cs ^ (srow & 7)) << 4) + (wt & 1) * 8;
            const uint32_t xoff = (8 * (lane >> 4) + (lane & 7)) * 128 + (((2 * w4 + ((lane >> 3) & 1)) ^ (lane & 7)) << 4);
            mbar_wait(BAR(B_W1SC));
            int slot = (8 * s) % NSLOT;
#pragma unroll 1
            for (int c = 0; c < 8; c++) {
                const uint32_t ta = sb + SM_Q + slot * 8192;
                mbar_wait(BAR(B_FULL + 8 * s + c));
                const uint32_t da = dlo(SM_Q + slot * 8192, 8192), db = dlo(SM_W1 + c * 8192, 8192);
                WG_FENCE();
#pragma unroll
                for (int k = 0; k < 4; k++) wgmma_ss64<1>(acc, da + 128 * k, db + 128 * k, (c | k) != 0);
                WG_COMMIT();
                const uint2 xv = lds64(ta + soff);
                const float2 cv = ldsf2(sb + SM_CS + (64 * c + srow) * 8);
                const float xx[4] = {blo(xv.x), bhi(xv.x), blo(xv.y), bhi(xv.y)};
#pragma unroll
                for (int t = 0; t < 4; t++) {
                    const float y = xx[t] * cv.x;
                    mo[6 * t] += xx[t]; mo[6 * t + 1] = fmaf(xx[t], xx[t], mo[6 * t + 1]); mo[6 * t + 2] += y;
                    mo[6 * t + 3] = fmaf(y, y, mo[6 * t + 3]); mo[6 * t + 4] = fmaf(y, cv.x, mo[6 * t + 4]); mo[6 * t + 5] = fmaf(y, cv.y, mo[6 * t + 5]);
                }
                if (c == cs) {
#pragma unroll
                    for (int n = 0; n < 4; n++) ldsm4t(x2p + 4 * n, ta + xoff + n * 2048);
                }
                if (c) { WG_WAIT(1); warp_arrive(BAR(B_EMPTY + 8 * s + c - 1)); }
                slot = slot == NSLOT - 1 ? 0 : slot + 1;
            }
            halve<24>(mo, 16, lane & 16); halve<12>(mo, 8, lane & 8); halve<6>(mo, 4, lane & 4);
            mo[0] += shx(mo[0], 2); mo[1] += shx(mo[1], 2); mo[2] += shx(mo[2], 2);
            const uint32_t red = sb + SM_RED + s * 768;
            if (!(lane & 2)) {
                const uint32_t a = red + w4 * 192 + 4 * (24 * (lane & 1) + 6 * (lane >> 3) + 3 * ((lane >> 2) & 1));
                stsf(a, mo[0]); stsf(a + 4, mo[1]); stsf(a + 8, mo[2]);
            }
            bar_sync(2 + s, 128);
            if (wt < 8) {
                float S[6];
#pragma unroll
                for (int k = 0; k < 3; k++) {
                    const uint32_t a = red + 24 * wt + 8 * k;
                    const float2 v0 = ldsf2(a), v1 = ldsf2(a + 192), v2 = ldsf2(a + 384), v3 = ldsf2(a + 576);
                    S[2 * k] = (v0.x + v1.x) + (v2.x + v3.x); S[2 * k + 1] = (v0.y + v1.y) + (v2.y + v3.y);
                }
                const uint4 k4 = lds128(sb + SM_CONST);
                const float Cc = __uint_as_float(k4.x), Cs = __uint_as_float(k4.y), Ccc = __uint_as_float(k4.z), Ccs = __uint_as_float(k4.w), Css = ldsf(sb + SM_CONST + 16);
                const float n1 = 1.f / 512.f;
                const float m1 = S[0] * n1, r1 = rsq(fmaxf(fmaf(-m1, m1, S[1] * n1), 0.f) + LN_EPS);
                const float m2 = fmaf(r1, fmaf(-m1, Cc, S[2]), Cs) * n1;
                const float e2 = (r1 * r1 * (S[3] - 2.f * m1 * S[4] + m1 * m1 * Ccc) + 2.f * r1 * fmaf(-m1, Ccs, S[5]) + Css) * n1;
                const float r2 = rsq(fmaxf(fmaf(-m2, m2, e2), 0.f) + LN_EPS), s1 = rcp(r1);
                str128(&G.stats1[64 * tau + 8 * cs + wt], make_uint4(tagw(split2(-m1), ep), tagw(split2(s1), ep), tagw(split2(-m2 * s1), ep), tagf(r1 * r2, ep)));
            }
            WG_WAIT(0);
            __syncwarp();
            if (lane == 0) { mbar_arrive(BAR(B_EMPTY + 8 * s + 7)); mbar_arrive(BAR(B_W1FREE)); }
            mbar_wait(BAR(B_U));
            uint4 s0, s1;
            do { s0 = ldr128(&G.stats1[row0]); s1 = ldr128(&G.stats1[row0 + 8]); } while (any(stale4(s0, ep) | stale4(s1, ep)));
            {
                const uint32_t a0 = q == 0 ? s0.x : q == 1 ? s0.y : q == 2 ? s0.z : 0u, a1 = q == 0 ? s1.x : q == 1 ? s1.y : q == 2 ? s1.z : 0u;
                WG_FENCE();
                wgmma_rs64<0>(acc, a0, a1, a0, a1, dlo(SM_U123, 1024), 1);
                WG_COMMIT();
            }
            const float al[2] = {__uint_as_float(s0.w), __uint_as_float(s1.w)};
            const float k0[2] = {GK0 * al[0], GK0 * al[1]}, k1[2] = {GK1 * al[0] * al[0] * al[0], GK1 * al[1] * al[1] * al[1]}, kh[2] = {0.5f * al[0], 0.5f * al[1]};
            WG_WAIT(0);
            pin<32>(acc);
            uint32_t gp[2][8];
#pragma unroll
            for (int r = 0; r < 2; r++)
#pragma unroll
                for (int n = 0; n < 8; n++) {
                    const float v0 = acc[4 * n + 2 * r], v1 = acc[4 * n + 2 * r + 1], h0 = kh[r] * v0, h1 = kh[r] * v1;
                    gp[r][n] = pack2(fmaf(h0, gelu_t(v0, k0[r], k1[r]), h0), fmaf(h1, gelu_t(v1, k0[r], k1[r]), h1));
                }
            bf16* go = G.g + (size_t)row0 * 512 + 64 * cs + 8 * q;
#pragma unroll
            for (int r = 0; r < 2; r++) {
                stg128(go + r * 4096, gp[r][0], gp[r][1], gp[r][2], gp[r][3]);
                stg128(go + r * 4096 + 32, gp[r][4], gp[r][5], gp[r][6], gp[r][7]);
            }
            bar_sync(2 + s, 128);
            if (wt == 0) asm volatile("st.release.gpu.global.b32 [%0], %1;" ::"l"(&G.flag[(tau * 8 + cs) * 32]), "r"(ep) : "memory");
            const float r1[2] = {rcp(blo(s0.y) + bhi(s0.y)), rcp(blo(s1.y) + bhi(s1.y))};
            const float c1[2] = {(blo(s0.x) + bhi(s0.x)) * r1[0], (blo(s1.x) + bhi(s1.x)) * r1[1]};
#pragma unroll
            for (int n = 0; n < 8; n++) {
                const uint4 cv = lds128(sb + SM_CS + (64 * cs + 8 * n + 2 * q) * 8);
#pragma unroll
                for (int r = 0; r < 2; r++) {
                    acc[4 * n + 2 * r] = fmaf(fmaf(blo(x2p[2 * n + r]), r1[r], c1[r]), __uint_as_float(cv.x), __uint_as_float(cv.y));
                    acc[4 * n + 2 * r + 1] = fmaf(fmaf(bhi(x2p[2 * n + r]), r1[r], c1[r]), __uint_as_float(cv.z), __uint_as_float(cv.w));
                }
            }
        }
        {
            mbar_wait(BAR(B_W2FULL));
            int slot = (16 + 8 * s) % NSLOT;
#pragma unroll 1
            for (int c = 0; c < 8; c++) {
                mbar_wait(BAR(B_FULL + 16 + 8 * s + c));
                const uint32_t da = dlo(SM_Q + slot * 8192, 16), db = dlo(SM_W2 + c * 8192, 8192);
                WG_FENCE();
#pragma unroll
                for (int k = 0; k < 4; k++) wgmma_ss64<0>(acc, da + 2 * k, db + 128 * k, 1);
                WG_COMMIT();
                if (c) { WG_WAIT(1); warp_arrive(BAR(B_EMPTY + 16 + 8 * s + c - 1)); }
                slot = slot == NSLOT - 1 ? 0 : slot + 1;
            }
            WG_WAIT(0);
            pin<32>(acc);
            __syncwarp();
            if (lane == 0) { mbar_arrive(BAR(B_EMPTY + 16 + 8 * s + 7)); mbar_arrive(BAR(B_W2FREE)); }
            bf16* xo = G.x1 + (size_t)row0 * 512 + 64 * cs + 8 * q;
            float sm[2] = {0.f, 0.f}, sq[2] = {0.f, 0.f};
#pragma unroll
            for (int r = 0; r < 2; r++)
#pragma unroll
                for (int h = 0; h < 2; h++) {
                    const float* a = acc + 16 * h + 2 * r;
                    stg128(xo + r * 4096 + 32 * h, pack2(a[0], a[1]), pack2(a[4], a[5]), pack2(a[8], a[9]), pack2(a[12], a[13]));
                }
#pragma unroll
            for (int i = 0; i < 32; i++) { sm[(i >> 1) & 1] += acc[i]; sq[(i >> 1) & 1] = fmaf(acc[i], acc[i], sq[(i >> 1) & 1]); }
#pragma unroll
            for (int r = 0; r < 2; r++) { sm[r] += shx(sm[r], 1); sq[r] += shx(sq[r], 1); sm[r] += shx(sm[r], 2); sq[r] += shx(sq[r], 2); }
            if (q < 2) G.stats2[2048 * cs + row0 + 8 * q] = q ? make_float2(sm[1], sq[1]) : make_float2(sm[0], sq[0]);
            bar_sync(2 + s, 128);
            if (wt == 0) asm volatile("st.release.gpu.global.b32 [%0], %1;" ::"l"(&G.flag[((32 + tau) * 8 + cs) * 32]), "r"(ep) : "memory");
#pragma unroll
            for (int n = 0; n < 8; n++) {
                const float2 gv = ldsf2(sb + SM_GB + (8 * n + 2 * q) * 4);
#pragma unroll
                for (int r = 0; r < 2; r++) {
                    acc[4 * n + 2 * r] = fmaf(gv.x, acc[4 * n + 2 * r], blo(x2p[2 * n + r]));
                    acc[4 * n + 2 * r + 1] = fmaf(gv.y, acc[4 * n + 2 * r + 1], bhi(x2p[2 * n + r]));
                }
            }
        }
        uint32_t H[56];
        float hr[2];
        const uint32_t hbuf = sb + SM_Q + (s ? 0 : 4 * 8192) + wt * 16;
        {
            float e[112];
            int slot = (32 + 8 * s) % NSLOT;
#pragma unroll 1
            for (int c = 0; c < 8; c++) {
                mbar_wait(BAR(B_FULL + 32 + 8 * s + c));
                mbar_wait(BAR(B_WFULL + c));
                const uint32_t da = dlo(SM_Q + slot * 8192, 16), db = dlo(wstage(c), 2048);
                WG_FENCE();
#pragma unroll
                for (int k = 0; k < 4; k++) wgmma_ss224(e, da + 2 * k, db + 64 * (k & 1) + 896 * (k >> 1), (c | k) != 0);
                WG_COMMIT();
                if (c) { WG_WAIT(1); __syncwarp(); if (lane == 0) { mbar_arrive(BAR(B_EMPTY + 32 + 8 * s + c - 1)); mbar_arrive(BAR(B_WEMPTY + c - 1)); } }
                slot = slot == NSLOT - 1 ? 0 : slot + 1;
            }
            const float2* sp = G.stats2 + 4096 * q + row0;
            const uint2 p0 = ldr64(sp), p1 = ldr64(sp + 8), p2 = ldr64(sp + 2048), p3 = ldr64(sp + 2056);
            float sm[2] = {__uint_as_float(p0.x) + __uint_as_float(p2.x), __uint_as_float(p1.x) + __uint_as_float(p3.x)};
            float sq[2] = {__uint_as_float(p0.y) + __uint_as_float(p2.y), __uint_as_float(p1.y) + __uint_as_float(p3.y)};
            float k0[2], k1[2];
            uint32_t am[2];
#pragma unroll
            for (int r = 0; r < 2; r++) {
                sm[r] += shx(sm[r], 1); sq[r] += shx(sq[r], 1); sm[r] += shx(sm[r], 2); sq[r] += shx(sq[r], 2);
                const float m = sm[r] * (1.f / 512.f), r3 = rsq(fmaxf(fmaf(-m, m, sq[r] * (1.f / 512.f)), 0.f) + LN_EPS);
                k0[r] = GK0 * r3; k1[r] = GK1 * r3 * r3 * r3; hr[r] = 0.5f * r3;
                am[r] = q < 2 ? split2(-m) : 0u;
            }
            mbar_wait(BAR(B_U + 1));
            WG_FENCE();
            wgmma_rs224(e, am[0], am[1], 0u, 0u, dlo(SM_U4, 0), 1);
            WG_COMMIT();
            WG_WAIT(0);
            pin<112>(e);
            __syncwarp();
            if (lane == 0) { mbar_arrive(BAR(B_EMPTY + 32 + 8 * s + 7)); mbar_arrive(BAR(B_WEMPTY + 7)); }
            const uint32_t rbuf = mapa(hbuf, pr ^ 1), rbar = mapa(BAR(B_HFULL + s), pr ^ 1);
#pragma unroll
            for (int k = 0; k < 14; k++) {
#pragma unroll
                for (int i = 0; i < 4; i++) {
                    const float v0 = e[8 * k + 2 * i], v1 = e[8 * k + 2 * i + 1];
                    H[4 * k + i] = pack2(fmaf(v0, gelu_t(v0, k0[i & 1], k1[i & 1]), v0), fmaf(v1, gelu_t(v1, k0[i & 1], k1[i & 1]), v1));
                }
                if (k == 5) mbar_wait_cluster(BAR(B_HFREE + s));
                if (k >= 5) {
#pragma unroll
                    for (int j = (k == 5 ? 0 : k); j <= k; j++)
                        asm volatile("st.async.weak.shared::cluster.mbarrier::complete_tx::bytes.v4.b32 [%0], {%1,%2,%3,%4}, [%5];"
                                     ::"r"(rbuf + j * 2048), "r"(H[4 * j]), "r"(H[4 * j + 1]), "r"(H[4 * j + 2]), "r"(H[4 * j + 3]), "r"(rbar) : "memory");
                }
            }
        }
        {
            float X[32], Y[32];
            uint32_t Hp[56];
            uint4* pdst = G.part + (size_t)((gi * 8 + 4 * pr) * 6 + s) * 512 + wt;
#define TILE(D, A, j, first) { mbar_wait(BAR(B_WFULL + 8 + (j))); WG_FENCE(); \
            _Pragma("unroll") for (int k = 0; k < 14; k++) wgmma_rs64<1>(D, A[4 * k], A[4 * k + 1], A[4 * k + 2], A[4 * k + 3], dlo(wstage(j), 8192) + 128 * k, !(first) || k != 0); \
            WG_COMMIT(); if ((j) && (j) != 5) WG_WAIT(1); if ((j) && (j) < 5) warp_arrive(BAR(B_WEMPTY + 7 + (j))); }
#define SEND(D, st_) { pin<32>(D); uint4* pd = pdst + (((pa + (st_)) & 3) * 6 + 2 * ((st_) - 1)) * 512; \
            _Pragma("unroll") for (int v = 0; v < 4; v++) str128(pd + 128 * v, make_uint4(tagw(pack2(D[8 * v], D[8 * v + 1]), ep), tagw(pack2(D[8 * v + 2], D[8 * v + 3]), ep), \
                                                                 tagw(pack2(D[8 * v + 4], D[8 * v + 5]), ep), tagw(pack2(D[8 * v + 6], D[8 * v + 7]), ep))); }
            pinu<56>(H);
            TILE(X, H, 0, true)
            TILE(Y, H, 1, true)
            mbar_wait_cluster(BAR(B_HFULL + s));
#pragma unroll
            for (int k = 0; k < 14; k++) {
                const uint4 v = lds128(hbuf + k * 2048); Hp[4 * k] = v.x; Hp[4 * k + 1] = v.y; Hp[4 * k + 2] = v.z; Hp[4 * k + 3] = v.w;
                if (k < 8) sts128(hbuf + k * 2048, make_uint4(__float_as_uint(acc[4 * k]), __float_as_uint(acc[4 * k + 1]), __float_as_uint(acc[4 * k + 2]), __float_as_uint(acc[4 * k + 3])));
            }
            pinu<56>(Hp);
            TILE(X, Hp, 2, false)
            TILE(Y, Hp, 3, false)
            SEND(X, 1)
            TILE(X, H, 4, true)
            SEND(Y, 2)
            TILE(X, Hp, 5, false)
            TILE(Y, H, 6, true)
            SEND(X, 3)
            TILE(Y, Hp, 7, false)
            const uint4* psrc = pdst + pa * 6 * 512;
            uint4 pv[12];
            uint32_t bad;
            do {
                bad = 0;
#pragma unroll
                for (int i = 0; i < 12; i++) pv[i] = ldr128(psrc + (i >> 2) * 1024 + (i & 3) * 128);
#pragma unroll
                for (int i = 0; i < 12; i++) bad |= stale4(pv[i], ep);
            } while (any(bad));
#pragma unroll
            for (int v = 0; v < 4; v++) {
                const uint32_t a[4] = {pv[v].x, pv[v].y, pv[v].z, pv[v].w}, c[4] = {pv[4 + v].x, pv[4 + v].y, pv[4 + v].z, pv[4 + v].w},
                               d[4] = {pv[8 + v].x, pv[8 + v].y, pv[8 + v].z, pv[8 + v].w};
#pragma unroll
                for (int i = 0; i < 4; i++) {
                    const float2 gv = ldsf2(sb + SM_GB + (16 * v + 8 * (i >> 1) + 2 * q) * 4);
                    const int j = 8 * v + 2 * i;
                    if (!(i & 1)) {
                        const uint4 t = lds128(hbuf + (2 * v + (i >> 1)) * 2048);
                        acc[j] = __uint_as_float(t.x); acc[j + 1] = __uint_as_float(t.y); acc[j + 2] = __uint_as_float(t.z); acc[j + 3] = __uint_as_float(t.w);
                    }
                    X[j] = gv.x * hr[i & 1]; X[j + 1] = gv.y * hr[i & 1];
                    acc[j] = fmaf(X[j], blo(a[i]) + blo(c[i]) + blo(d[i]), acc[j]);
                    acc[j + 1] = fmaf(X[j + 1], bhi(a[i]) + bhi(c[i]) + bhi(d[i]), acc[j + 1]);
                }
            }
            WG_WAIT(0);
            pin<32>(Y);
            const uint32_t stg = sb + SM_Q + 8 * 8192 + warp * 2048;
            const int srow = (lane & 7) + 8 * ((lane >> 3) & 1);
#pragma unroll
            for (int n2 = 0; n2 < 4; n2++) {
                uint32_t o[4];
#pragma unroll
                for (int i = 0; i < 4; i++) { const int j = 8 * n2 + 2 * i; o[i] = pack2(fmaf(X[j], Y[j], acc[j]), fmaf(X[j + 1], Y[j + 1], acc[j + 1])); }
                stsm4(stg + srow * 128 + (((2 * n2 + (lane >> 4)) ^ (lane & 7)) << 4), o[0], o[1], o[2], o[3]);
            }
            __syncwarp();
            bf16* oo = P.out + (size_t)(64 * tau + 16 * w4 + (lane >> 3)) * 512 + 64 * cs + 8 * (lane & 7);
#pragma unroll
            for (int i = 0; i < 4; i++) {
                const int r = 4 * i + (lane >> 3);
                const uint4 v = lds128(stg + r * 128 + (((lane & 7) ^ (r & 7)) << 4));
                stg128(oo + i * 2048, v.x, v.y, v.z, v.w);
            }
            if (tid == 128) str32(&G.epoch[b], ep);
            warp_arrive(BAR(B_DONE));
#undef TILE
#undef SEND
        }
    } else {
        asm volatile("setmaxnreg.dec.sync.aligned.u32 56;");
        const int at = tid - 256, aw = warp - 8;
        uint4 xr[2][4];
        {
            const bf16* p = P.x + (size_t)(16 * b + g) * 512 + 128 * aw + 8 * q;
#pragma unroll
            for (int i = 0; i < 4; i++) { xr[0][i] = ldg128(p + 32 * i); xr[1][i] = ldg128(p + 4096 + 32 * i); }
        }
        const uint32_t cw = ldg32(P.c + 64 * (b & 7) + 2 * lane);
        const uint32_t ep = ldr32(&G.epoch[b]) + 1;
        const int mcol = 64 * ((b >> 3) & 7) + 512 * (b >> 6);
        if (aw == 0) {
            if (lane == 0) {
#pragma unroll
                for (int i = 0; i < B_EARLY; i++) { mbar_init(BAR(i), 1); mbar_expect(BAR(i), i < B_XC ? 8192 : 16384); }
                asm volatile("fence.mbarrier_init.release.cluster;" ::: "memory");
            }
            __syncwarp();
            asm volatile("barrier.cluster.arrive.relaxed.aligned;" ::: "memory");
            if (lane == 0) tma2d(sb + SM_WM, &M.m[tmWm], mcol, 64 * (b & 7), BAR(B_WM));
            asm volatile("barrier.cluster.wait.aligned;" ::: "memory");
            if (lane == 0) {
#pragma unroll 1
                for (int i = 0; i < 4; i++)
                    tma2d_pair(sb + SM_XC + (2 * i + pr) * 4096, &M.m[tmXc], 8 * (b >> 1), 256 * (2 * i + pr), BAR(B_XC + (i >> 1)));
            }
        } else {
            asm volatile("barrier.cluster.arrive.relaxed.aligned;" ::: "memory");
            if (lane == 0) {
                if (aw == 2) {
#pragma unroll
                    for (int i = B_WFULL; i < B_NEAR; i++) mbar_init(BAR(i), i < B_WEMPTY ? 1 : i < B_CONV ? 8 : 4);
                    sts128(sb + SM_ONE, make_uint4(0x3F803F80u, 0x3F803F80u, 0x3F803F80u, 0x3F803F80u));
                } else {
                    const uint32_t b1 = BAR(aw == 1 ? B_FULL + 48 : B_EMPTY + 48);
                    uint32_t b0 = BAR(aw == 1 ? B_FULL : B_NEAR);
                    do {
#pragma unroll
                        for (int k = 0; k < 8; k++) mbar_init(b0 + 8 * k, aw == 1 ? 1 : 4);
                        b0 += 64;
                    } while (b0 != b1);
                }
                asm volatile("fence.mbarrier_init.release.cluster;" ::: "memory");
            }
            __syncwarp();
            if (aw == 1) { mbar_expect(BAR(B_FULL + lane), 8192); if (lane < 16) mbar_expect(BAR(B_FULL + 32 + lane), 8192); }
            if (aw == 2 && lane < 20) mbar_expect(BAR(B_WFULL + lane), lane < 18 ? 28672 : 65536);
            if (aw == 3 && lane == 0) {
#pragma unroll 1
                for (int i = 0; i < tmCount; i++) asm volatile("prefetch.tensormap [%0];" ::"l"(&M.m[i]) : "memory");
            }
        }
        asm volatile("bar.arrive 5, 384;" ::: "memory");
        {
            const float c0 = blo(cw), c1 = bhi(cw);
            sts32(sb + SM_SCV + aw * 128 + vecpos(lane), pack2(__fdividef(c0, 1.f + __expf(-c0)), __fdividef(c1, 1.f + __expf(-c1))));
        }
        {
            float ds[4] = {0.f, 0.f, 0.f, 0.f}, d0[4] = {0.f, 0.f, 0.f, 0.f}, d1[4] = {0.f, 0.f, 0.f, 0.f};
#pragma unroll
            for (int i = 0; i < 4; i++) {
                const uint4 R = xr[0][i], S = xr[1][i];
                mma(ds, R.x, S.x, R.y, S.y, 0x3F803F80u, 0x3F803F80u); mma(d0, R.x, S.x, R.y, S.y, R.x, R.y); mma(d1, R.x, S.x, R.y, S.y, S.x, S.y);
                mma(ds, R.z, S.z, R.w, S.w, 0x3F803F80u, 0x3F803F80u); mma(d0, R.z, S.z, R.w, S.w, R.z, R.w); mma(d1, R.z, S.z, R.w, S.w, S.z, S.w);
            }
            if (q == (g >> 1)) {
                const uint32_t a = sb + SM_ARED + aw * 128 + g * 8;
                sts64(a, __float_as_uint(ds[0]), __float_as_uint((g & 1) ? d0[1] : d0[0]));
                sts64(a + 64, __float_as_uint(ds[2]), __float_as_uint((g & 1) ? d1[3] : d1[2]));
            }
            bar_sync(4, 128);
            if (aw == 3 && lane < 16) {
                const uint32_t a = sb + SM_ARED + lane * 8;
                const float2 v0 = ldsf2(a), v1 = ldsf2(a + 128), v2 = ldsf2(a + 256), v3 = ldsf2(a + 384);
                const float m = ((v0.x + v1.x) + (v2.x + v3.x)) * (1.f / 512.f), e2 = ((v0.y + v1.y) + (v2.y + v3.y)) * (1.f / 512.f);
                const float r = rsq(fmaxf(fmaf(-m, m, e2), 0.f) + LN_EPS);
                str64(&G.stats0[16 * b + lane], tagf(r, ep), tagf(-m * r, ep));
            }
        }
        if (aw < 3) {
            const uint4 a0 = lds128(sb + SM_SCV + aw * 128 + q * 16), a1 = lds128(sb + SM_SCV + aw * 128 + 64 + q * 16);
            const uint32_t ta = sb + SM_WM + aw * 8192 + lane * 128;
            const int col = mcol + (aw ? 512 * (b >> 6) + 512 + 512 * aw : 0);
            if (aw && lane == 0) tma2d(sb + SM_WM + 8192 * aw, &M.m[tmWm], col, 64 * (b & 7), BAR(B_WM + aw));
            float t0 = 0.f, t1 = 0.f;
            mbar_wait_b(BAR(B_WM + aw));
#pragma unroll 2
            for (int n = 0; n < 8; n++) {
                uint32_t b0[4], b1[4];
                ldsm4t(b0, ta + ((n ^ (lane & 7)) << 4)); ldsm4t(b1, ta + 4096 + ((n ^ (lane & 7)) << 4));
                float du[4] = {0.f, 0.f, 0.f, 0.f}, dl[4] = {0.f, 0.f, 0.f, 0.f};
                mma(du, a0.x, a0.y, a0.z, a0.w, b0[0], b0[1]); mma(dl, a0.x, a0.y, a0.z, a0.w, b0[2], b0[3]);
                mma(du, a1.x, a1.y, a1.z, a1.w, b1[0], b1[1]); mma(dl, a1.x, a1.y, a1.z, a1.w, b1[2], b1[3]);
                if (n == g) { t0 = du[0] + dl[2]; t1 = du[1] + dl[3]; }
            }
            str64(&G.modq[3072 * (b & 7) + col + 2 * lane], tagf(t0, ep), tagf(t1, ep));
            if (at == 0) {
                mbar_wait(BAR(B_MOD));
                if (b < 112) { tma2d(sb + SM_W3C, &M.m[tmW3c], 16 * b, 0, BAR(B_W3C)); tma2d(sb + SM_W3C + 8192, &M.m[tmW3c], 16 * b, 256, BAR(B_W3C)); }
                l2_prefetch(P.w2 + (size_t)b * 2048, 4096);
                l2_prefetch(P.w4 + (size_t)b * 7168, 14336);
            }
            if (aw == 1 && lane < 16) str128(&G.stats1[1024 * (lane >> 3) + 64 * gi + 8 * cs + (lane & 7)], make_uint4(ep + 1, ep + 1, ep + 1, ep + 1));
        } else {
#pragma unroll 1
            for (int rd = 0; rd < 2; rd++) {
                const int v = rd ? 2 + (lane >> 3) : (lane >> 3) & 1;
                uint4 w; int it = 0;
                do { w = ldr128(&G.modq[3072 * (lane & 7) + 512 * v + 4 * b]); if (++it > SPIN_MAX) __trap(); } while (any(stale4(w, ep)));
                float t[4] = {__uint_as_float(w.x), __uint_as_float(w.y), __uint_as_float(w.z), __uint_as_float(w.w)};
                const float one = (v == 1 || v == 4) ? 1.f : 0.f;
#pragma unroll
                for (int i = 0; i < 4; i++) {
                    t[i] += shx(t[i], 1); t[i] += shx(t[i], 2); t[i] += shx(t[i], 4);
                    t[i] = bround(one + bround(t[i]));
                }
                if (!(lane & 7)) {
                    if (v < 3) sts128(sb + SM_OWN + 16 * v, make_uint4(__float_as_uint(t[0]), __float_as_uint(t[1]), __float_as_uint(t[2]), __float_as_uint(t[3])));
                    if (rd) str128(&G.modp[4 * b + v - 2], make_uint4(tagf(t[0], ep), tagf(t[1], ep), tagf(t[2], ep), tagf(t[3], ep)));
                }
                warp_arrive(BAR(B_MOD + rd));
            }
        }
#pragma unroll 1
        for (int rd = 0; rd < 2; rd++) {
            if (rd == 1) {
                uint4 vs, vc, vg; int it = 0;
                do {
                    vs = ldr128(&G.modp[4 * at + 1]); vc = ldr128(&G.modp[4 * at + 2]); vg = ldr128(&G.modp[4 * at + 3]);
                    if (++it > SPIN_MAX) __trap();
                } while (any(stale4(vs, ep) | stale4(vc, ep) | stale4(vg, ep)));
                const uint32_t vp = sb + SM_CBV + vecpos(2 * at);
                sts32(vp, prmt(vc.x, vc.y, 0x7632u)); sts32(vp + 16, prmt(vc.z, vc.w, 0x7632u));
                sts32(vp + 1024, prmt(vs.x, vs.y, 0x7632u)); sts32(vp + 1040, prmt(vs.z, vs.w, 0x7632u));
                const float sv[4] = {bhi(vs.x), bhi(vs.y), bhi(vs.z), bhi(vs.w)}, cv[4] = {bhi(vc.x), bhi(vc.y), bhi(vc.z), bhi(vc.w)};
                sts128(sb + SM_CS + at * 32, make_uint4(__float_as_uint(cv[0]), __float_as_uint(sv[0]), __float_as_uint(cv[1]), __float_as_uint(sv[1])));
                sts128(sb + SM_CS + at * 32 + 16, make_uint4(__float_as_uint(cv[2]), __float_as_uint(sv[2]), __float_as_uint(cv[3]), __float_as_uint(sv[3])));
                if ((at >> 4) == cs) sts128(sb + SM_GB + (at & 15) * 16, make_uint4(vg.x & ~1u, vg.y & ~1u, vg.z & ~1u, vg.w & ~1u));
                float v[8] = {0.f, 0.f, 0.f, 0.f, 0.f, 0.f, 0.f, 0.f};
#pragma unroll
                for (int i = 0; i < 4; i++) {
                    v[0] += cv[i]; v[1] += sv[i]; v[2] = fmaf(cv[i], cv[i], v[2]); v[3] = fmaf(cv[i], sv[i], v[3]); v[4] = fmaf(sv[i], sv[i], v[4]);
                }
                halve<8>(v, 16, lane & 16); halve<4>(v, 8, lane & 8); halve<2>(v, 4, lane & 4);
                v[0] += shx(v[0], 2); v[0] += shx(v[0], 1);
                stsf(sb + SM_ARED + 512 + aw * 32 + g * 4, v[0]);
                bar_sync(4, 128);
                if (at < 5) { const uint32_t a = sb + SM_ARED + 512 + at * 4; stsf(sb + SM_CONST + 4 * at, (ldsf(a) + ldsf(a + 32)) + (ldsf(a + 64) + ldsf(a + 96))); }
            }
            if (rd ? (aw == 2 && gi < 8) : (aw < 2 && b < 112)) {
                uint32_t ba = rd ? sb + SM_W1 + lane * 128 + ((gi ^ (lane & 7)) << 4) : sb + SM_W3C + lane * 32 + aw * 16;
                uint32_t aa = rd && g < 2 ? sb + SM_CBV + g * 1024 + q * 16 : sb + SM_ONE;
                const uint32_t bstep = rd ? 4096 : 1024, astep = rd && g < 2 ? 64 : 0;
                mbar_wait_b(BAR(rd ? B_W1FULL : B_W3C));
                float du[4] = {0.f, 0.f, 0.f, 0.f}, dl[4] = {0.f, 0.f, 0.f, 0.f};
#pragma unroll 2
                for (int i = 0; i < 16; i++) {
                    uint32_t bb[4];
                    ldsm4t(bb, ba); const uint4 a = lds128(aa);
                    mma(du, a.x, a.y, a.z, a.w, bb[0], bb[1]); mma(dl, a.x, a.y, a.z, a.w, bb[2], bb[3]);
                    ba += bstep; aa += astep;
                }
                if (g < (rd ? 3 : 1)) str64(rd ? &G.u123[512 * g + 64 * cs + 8 * gi + 2 * q] : &G.u4[16 * b + 8 * aw + 2 * q], tagf(du[0] + dl[2], ep), tagf(du[1] + dl[3], ep));
            }
        }
        mbar_wait_b(BAR(B_W1FULL));
        warp_arrive(BAR(B_W1RDY));
        if (aw < 2) {
            const int s = aw, tau = 16 * s + gi, c = lane & 7;
            const int sh = (c & 4 ? 2 : 1) * (c & 2 ? 1 : -1);
            mbar_wait(BAR(B_CONV + s));
            if (lane == 0) asm volatile("red.release.gpu.global.add.u32 [%0], 1;" ::"l"(&G.cnt[(8 * s + (b >> 4)) * 32]) : "memory");
            __syncwarp();
#pragma unroll 1
            for (int ph = 0; ph < 3; ph++) {
                const uint32_t* fp; uint32_t target = ep; bool need = lane < 8;
                if (ph == 0) { fp = &G.cnt[((tau < 18 ? 0 : 8) + c) * 32]; target = 16 * ep; }
                else if (ph == 1) {
                    const int tn = lane < 8 ? tau : tau + (sh > 0 ? 1 : -1);
                    need = lane < 16 && tn >= 0 && tn < 32;
                    fp = &G.flag[((need ? tn : tau) * 8 + c) * 32];
                } else fp = &G.flag[((32 + tau) * 8 + c) * 32];
                const CUtensorMap* tm = &M.m[tmX2 + ph];
                const int n = 16 * ph + 8 * s + c;
                const uint32_t dst = sb + SM_Q + (n % NSLOT) * 8192;
                const int c0 = ph == 0 ? 64 * tau : 64 * c, c1 = ph == 0 ? 64 * c : 64 * tau + (ph == 1 ? sh : 0);
                bool pend = lane < 8, room = n < NSLOT;
                for (;;) {
                    if (need) need = (int)(ldr32(fp) - target) < 0;
                    if (pend && !room) room = mbar_test(BAR(B_EMPTY + n - NSLOT));
                    uint32_t m = __ballot_sync(0xffffffffu, need);
                    if (pend && room && !((m >> c) & 0x101)) {
                        fence_acquire(); fence_async_global();
                        tma2d(dst, tm, c0, c1, BAR(B_FULL + n));
                        pend = false;
                    }
                    if (!__any_sync(0xffffffffu, pend)) break;
                    if (!m) __nanosleep(40);
                }
            }
            if (lane == 0) {
                mbar_wait(BAR(B_EMPTY + 39 + 8 * s));
                if (s == 0) mbar_wait(BAR(B_EMPTY + 40));
                mbar_arrive_remote(mapa(BAR(B_HFREE + s), pr ^ 1));
            }
        } else if (aw == 2) {
            {
                uint2 v[3];
                do {
#pragma unroll
                    for (int k = 0; k < 3; k++) v[k] = ldr64(&G.u123[512 * k + 64 * cs + 2 * lane]);
                } while (any(stale2(v[0], ep) | stale2(v[1], ep) | stale2(v[2], ep)));
#pragma unroll
                for (int h = 0; h < 2; h++) {
                    const uint32_t w0 = split2(__uint_as_float(h ? v[0].y : v[0].x)), w1 = split2(__uint_as_float(h ? v[1].y : v[1].x)), w2 = split2(__uint_as_float(h ? v[2].y : v[2].x));
                    const uint32_t a = sb + SM_U123 + 32 * lane + 16 * h;
                    sts128(a, make_uint4(prmt(w0, w0, 0x3232u), prmt(w1, w1, 0x3232u), prmt(w2, w2, 0x3232u), 0u));
                    sts128(a + 1024, make_uint4(prmt(w0, w0, 0x1010u), prmt(w1, w1, 0x1010u), prmt(w2, w2, 0x1010u), 0u));
                }
                fence_async_smem();
                warp_arrive(BAR(B_U));
            }
            if (lane == 0) {
                mbar_wait(BAR(B_CONV + 1));
                fence_async_smem();
                tma5d(sb + SM_W2, &M.m[tmW2], 64 * cs, 0, 0, 0, 0, BAR(B_W2FULL));
#pragma unroll 1
                for (int t = 0; t < 8; t++) {
                    mbar_wait(BAR(t < 2 ? B_W1FREE : t < 4 ? B_W2FREE : B_WEMPTY + t - 4));
                    tma5d(sb + wstage(t), &M.m[tmW3], 0, 0, 8 * t, 0, 7 * fs, BAR(B_WFULL + t));
                    tma5d(sb + wstage(t) + 14336, &M.m[tmW3], 0, 0, 8 * t + 4, 0, 7 * fs, BAR(B_WFULL + t));
                }
#pragma unroll 1
                for (int j = 0; j < 8; j++) {
                    const int jj = (j == 1 || j == 2) ? 3 - j : j;
                    const int c0 = 64 * (4 * pr + ((pa + (jj >> 1) + 1) & 3)), c1 = 224 * (fs ^ (jj & 1));
                    mbar_wait(BAR(B_WEMPTY + 4 + j));
                    tma2d(sb + wstage(j), &M.m[tmW4], c0, c1, BAR(B_WFULL + 8 + j));
                }
            }
        } else {
            if ((sb & 0x3FFFF) != SMEM_BASE) __trap();
            mbar_wait_b(BAR(B_W1FREE));
#pragma unroll 1
            for (int n = lane; n < 224; n += 32) {
                uint32_t v; int it = 0;
                do { v = ldr32(&G.u4[224 * fs + n]); if (++it > SPIN_MAX) __trap(); } while (any(v ^ ep));
                v = split2(__uint_as_float(v));
                sts128(sb + SM_U4 + 16 * n, make_uint4(prmt(v, v, 0x3232u), prmt(v, v, 0x1010u), 0u, 0u));
            }
            fence_async_smem();
            warp_arrive(BAR(B_U + 1));
            mbar_wait_b(BAR(B_DONE));
        }
    }
}

typedef CUresult (*EncodeFn)(CUtensorMap*, CUtensorMapDataType, cuuint32_t, void*, const cuuint64_t*, const cuuint64_t*,
                             const cuuint32_t*, const cuuint32_t*, CUtensorMapInterleave, CUtensorMapSwizzle,
                             CUtensorMapL2promotion, CUtensorMapFloatOOBfill);

void encode(EncodeFn fn, CUtensorMap* m, const void* base, int rank, const cuuint64_t* dim, const cuuint64_t* stride,
            const cuuint32_t* box, CUtensorMapSwizzle sw) {
    const cuuint32_t es[5] = {1, 1, 1, 1, 1};
    fn(m, CU_TENSOR_MAP_DATA_TYPE_BFLOAT16, rank, const_cast<void*>(base), dim, stride, box, es, CU_TENSOR_MAP_INTERLEAVE_NONE,
       sw, CU_TENSOR_MAP_L2_PROMOTION_L2_128B, CU_TENSOR_MAP_FLOAT_OOB_FILL_NONE);
}

}

extern "C" void kernel_launch(void* const* d_in, const int* in_sizes, int n_in, void* d_out, int out_size) {
    (void)in_sizes; (void)n_in; (void)out_size;
    Params P;
    P.x = (const bf16*)d_in[0]; P.Are = (const bf16*)d_in[1]; P.Aim = (const bf16*)d_in[2]; P.Bre = (const bf16*)d_in[3];
    P.Bim = (const bf16*)d_in[4]; P.Cre = (const bf16*)d_in[5]; P.Cim = (const bf16*)d_in[6]; P.logdt = (const bf16*)d_in[7];
    P.dskip = (const bf16*)d_in[8]; P.w1 = (const bf16*)d_in[10]; P.w2 = (const bf16*)d_in[11]; P.w3 = (const bf16*)d_in[12];
    P.w4 = (const bf16*)d_in[13]; P.c = (const bf16*)d_in[14]; P.wmod = (const bf16*)d_in[15]; P.out = (bf16*)d_out;

    void* fnp = nullptr;
    cudaDriverEntryPointQueryResult qr;
    cudaGetDriverEntryPoint("cuTensorMapEncodeTiled", &fnp, cudaEnableDefault, &qr);
    EncodeFn fn = (EncodeFn)fnp;
    cudaFuncSetAttribute(fused_kernel, cudaFuncAttributeMaxDynamicSharedMemorySize, SM_TOTAL);
    void* pgs;
    cudaGetSymbolAddress(&pgs, G);
    const Scratch* gs = (const Scratch*)pgs;
    const void *px2 = gs->x2t, *pg = gs->g, *px1 = gs->x1;
    Maps M;
    { const cuuint64_t d[2] = {2048, 512}, st[1] = {4096}; const cuuint32_t bx[2] = {64, 64}; encode(fn, &M.m[tmX2], px2, 2, d, st, bx, CU_TENSOR_MAP_SWIZZLE_128B); }
    { const cuuint64_t d[2] = {512, 2048}, st[1] = {1024}; const cuuint32_t bx[2] = {64, 64};
      encode(fn, &M.m[tmG], pg, 2, d, st, bx, CU_TENSOR_MAP_SWIZZLE_128B); encode(fn, &M.m[tmX1], px1, 2, d, st, bx, CU_TENSOR_MAP_SWIZZLE_128B); }
    { const cuuint64_t d[2] = {512, 512}, st[1] = {1024}; const cuuint32_t bx[2] = {64, 256}; encode(fn, &M.m[tmW1], P.w1, 2, d, st, bx, CU_TENSOR_MAP_SWIZZLE_128B); }
    { const cuuint64_t d[5] = {512, 2, 4, 4, 16}, st[4] = {1024, 8192, 2048, 32768}; const cuuint32_t bx[5] = {64, 2, 4, 4, 16};
      encode(fn, &M.m[tmW2], P.w2, 5, d, st, bx, CU_TENSOR_MAP_SWIZZLE_128B); }
    { const cuuint64_t d[5] = {32, 2, 64, 4, 56}, st[4] = {3584, 8 * 3584, 2 * 3584, 64}; const cuuint32_t bx[5] = {32, 2, 4, 4, 7};
      encode(fn, &M.m[tmW3], P.w3, 5, d, st, bx, CU_TENSOR_MAP_SWIZZLE_64B); }
    { const cuuint64_t d[2] = {512, 1792}, st[1] = {1024}; const cuuint32_t bx[2] = {64, 224}; encode(fn, &M.m[tmW4], P.w4, 2, d, st, bx, CU_TENSOR_MAP_SWIZZLE_128B); }
    { const cuuint64_t d[2] = {512, 2048}, st[1] = {1024}; const cuuint32_t bx[2] = {8, 256}; encode(fn, &M.m[tmXc], P.x, 2, d, st, bx, CU_TENSOR_MAP_SWIZZLE_NONE); }
    { const cuuint64_t d[2] = {3072, 512}, st[1] = {6144}; const cuuint32_t bx[2] = {64, 64}; encode(fn, &M.m[tmWm], P.wmod, 2, d, st, bx, CU_TENSOR_MAP_SWIZZLE_128B); }
    { const cuuint64_t d[2] = {1792, 512}, st[1] = {3584}; const cuuint32_t bx[2] = {16, 256}; encode(fn, &M.m[tmW3c], P.w3, 2, d, st, bx, CU_TENSOR_MAP_SWIZZLE_NONE); }

    cudaLaunchConfig_t cfg = {};
    cfg.gridDim = dim3(128); cfg.blockDim = dim3(384); cfg.dynamicSmemBytes = SM_TOTAL; cfg.stream = cudaStreamPerThread;
    cudaLaunchAttribute at[1];
    at[0].id = cudaLaunchAttributeClusterDimension; at[0].val.clusterDim.x = 2; at[0].val.clusterDim.y = 1; at[0].val.clusterDim.z = 1;
    cfg.attrs = at; cfg.numAttrs = 1;
    cudaLaunchKernelEx(&cfg, fused_kernel, P, M);
}
```

```cpp
#include <cuda_runtime.h>
#include <cuda_bf16.h>
#include <cuda.h>
#include <stdint.h>

namespace {

typedef __nv_bfloat16 bf16;

constexpr int SM_W1 = 0, SM_W2 = 65536, SM_Q = 131072, NSLOT = 11, SM_MISC = SM_Q + NSLOT * 8192;
constexpr int PT_PITCH = 272, PT_B = 24 * PT_PITCH + 1024;
constexpr int UW_B = 10880, SM_UW = SM_W2, XS_B = 10304, SM_XS = SM_UW + 4 * UW_B;
constexpr int WD_B = 3104, SM_WD = SM_Q, SM_SCV = SM_WD + 4 * WD_B;
constexpr int SM_ST = SM_W1, SM_W3C = SM_Q + 2 * 8192, SM_WM = SM_Q + 4 * 8192, SM_XC = SM_Q + 7 * 8192, SM_DEP = SM_XC;
constexpr int SM_U4 = SM_W1 + 57344;
constexpr int SM_H = SM_Q + 4 * 8192;
constexpr int SM_BAR = SM_MISC;
constexpr int SM_CBV = SM_BAR + 1152;
constexpr int SM_ONE = SM_CBV + 2048;
constexpr int SM_U123 = SM_ONE + 128;
constexpr int SM_GB = SM_U123 + 2048;
constexpr int SM_RED = SM_GB + 256;
constexpr int SM_ARED = SM_RED + 1536;
constexpr int SM_OWN = SM_ARED + 640;
constexpr int SM_CONST = SM_OWN + 64;
constexpr int SM_TS = SM_CONST + 64;
constexpr int SM_TOTAL = SM_TS + 384;
static_assert(SM_XS + 2 * XS_B <= SM_Q, "conv buffers");
static_assert(SM_TOTAL <= 232448, "smem");
constexpr int T0o = 8, T4o = 288, T2o = 432, TM2o = 512, T1o = 592, T3o = 640, T5o = 688, TM1o = 736;
constexpr int B_WM = 0  , B_XC = 3  , B_ST = 5, B_AUXQ = 6,
              B_FULL = 8  ,
              B_WFULL = 56  , B_HFULL = 72  , B_W1FULL = 74, B_W2FULL = 75, B_W3C = 76,
              B_MOD = 77  , B_U = 79  , B_SEEN = 81  , B_WEMPTY = 83  , B_DONE = 95,
              B_NEAR = 96  , B_EMPTY = 112  , B_TILE = 128  , B_CONV = 132  ,
              B_UB = 134  , B_HFREE = 136  , B_W1RDY = 138, B_W1SC = 139;

constexpr float LN_EPS = 1e-5f;
constexpr int SPIN_MAX = 1 << 20;

struct Scratch {
    bf16 x2t[512 * 2048], g[2048 * 512], x1[2048 * 512];
    uint4 part[16 * 8 * 3 * 2 * 512];
    uint4 stats1[2048];
    float2 stats2[2048 * 8];
    uint2 stats0[2048];
    uint32_t modq[8 * 3072];
    uint4 modp[128 * 4];
    uint32_t u123[3 * 512], u4[1792];
    uint32_t cnt[2 * 8 * 32], flag[2 * 32 * 8 * 32], epoch[128];
};
__device__ __align__(1024) Scratch g_scratch;

struct Params {
    const bf16 *x, *Are, *Aim, *Bre, *Bim, *Cre, *Cim, *logdt, *dskip, *w1, *w2, *w3, *w4, *c, *wmod;
    bf16* out;
    Scratch* gs;
};

enum { tmX2, tmG, tmX1, tmWm, tmXc, tmW3c, tmW1, tmW2, tmW3, tmW4, tmCount };
struct Maps { CUtensorMap m[tmCount]; };

__device__ __forceinline__ void mbar_init(uint32_t b, int c) { asm volatile("mbarrier.init.shared::cta.b64 [%0], %1;" ::"r"(b), "r"(c) : "memory"); }
__device__ __forceinline__ void mbar_expect(uint32_t b, int bytes) { asm volatile("mbarrier.arrive.expect_tx.shared::cta.b64 _, [%0], %1;" ::"r"(b), "r"(bytes) : "memory"); }
__device__ __forceinline__ void mbar_arrive(uint32_t b) { asm volatile("mbarrier.arrive.shared::cta.b64 _, [%0];" ::"r"(b) : "memory"); }
__device__ __forceinline__ void mbar_arrive_remote(uint32_t b) { asm volatile("mbarrier.arrive.relaxed.cluster.shared::cluster.b64 _, [%0];" ::"r"(b) : "memory"); }
__device__ __forceinline__ bool mbar_test(uint32_t b) {
    uint32_t ok;
    asm volatile("{.reg .pred p; mbarrier.test_wait.parity.shared::cta.b64 p, [%1], 0; selp.u32 %0, 1, 0, p;}" : "=r"(ok) : "r"(b) : "memory");
    return ok;
}
__device__ __forceinline__ void mbar_wait(uint32_t b) {
    asm volatile("{.reg .pred p; W: mbarrier.try_wait.parity.shared::cta.b64 p, [%0], 0; @!p bra W;}" ::"r"(b) : "memory");
}
__device__ __forceinline__ void mbar_wait_cluster(uint32_t b) {
    asm volatile("{.reg .pred p; W: mbarrier.try_wait.parity.acquire.cluster.shared::cta.b64 p, [%0], 0; @!p bra W;}" ::"r"(b) : "memory");
}
__device__ __forceinline__ void mbar_wait_b(uint32_t b) {
    uint32_t ok; int it = 0;
    do {
        asm volatile("{.reg .pred p; mbarrier.try_wait.parity.shared::cta.b64 p, [%1], 0; selp.u32 %0, 1, 0, p;}" : "=r"(ok) : "r"(b) : "memory");
        if (++it > SPIN_MAX) __trap();
    } while (!ok);
}
__device__ __forceinline__ bool any(uint32_t bad) { return __any_sync(0xffffffffu, bad & 1); }
__device__ __forceinline__ void warp_arrive(uint32_t b) { __syncwarp(); if ((threadIdx.x & 31) == 0) mbar_arrive(b); }
__device__ __forceinline__ void bar_sync(int id, int n) { asm volatile("bar.sync %0, %1;" ::"r"(id), "r"(n) : "memory"); }
__device__ __forceinline__ void fence_async_smem() { asm volatile("fence.proxy.async.shared::cta;" ::: "memory"); }
__device__ __forceinline__ void fence_acquire() { asm volatile("fence.acquire.gpu;" ::: "memory"); }
__device__ __forceinline__ void fence_async_global() { asm volatile("fence.proxy.async.global;" ::: "memory"); }
__device__ __forceinline__ uint32_t mapa(uint32_t a, uint32_t r) { uint32_t d; asm("mapa.shared::cluster.u32 %0, %1, %2;" : "=r"(d) : "r"(a), "r"(r)); return d; }

__device__ __forceinline__ void tma2d(uint32_t dst, const CUtensorMap* m, int c0, int c1, uint32_t bar) {
    asm volatile("cp.async.bulk.tensor.2d.shared::cluster.global.mbarrier::complete_tx::bytes [%0], [%1, {%3, %4}], [%2];"
                 ::"r"(dst), "l"(m), "r"(bar), "r"(c0), "r"(c1) : "memory");
}
__device__ __forceinline__ void tma2d_pair(uint32_t dst, const CUtensorMap* m, int c0, int c1, uint32_t bar) {
    asm volatile("cp.async.bulk.tensor.2d.shared::cluster.global.mbarrier::complete_tx::bytes.multicast::cluster [%0], [%1, {%3, %4}], [%2], %5;"
                 ::"r"(dst), "l"(m), "r"(bar), "r"(c0), "r"(c1), "h"((unsigned short)3) : "memory");
}
__device__ __forceinline__ void tma5d(uint32_t dst, const CUtensorMap* m, int c0, int c1, int c2, int c3, int c4, uint32_t bar) {
    asm volatile("cp.async.bulk.tensor.5d.shared::cluster.global.mbarrier::complete_tx::bytes [%0], [%1, {%3, %4, %5, %6, %7}], [%2];"
                 ::"r"(dst), "l"(m), "r"(bar), "r"(c0), "r"(c1), "r"(c2), "r"(c3), "r"(c4) : "memory");
}
__device__ __forceinline__ void l2_prefetch(const void* p, int bytes) { asm volatile("cp.async.bulk.prefetch.L2.global [%0], %1;" ::"l"(p), "r"(bytes) : "memory"); }

__device__ __forceinline__ uint32_t lds32(uint32_t a) { uint32_t v; asm volatile("ld.shared.b32 %0, [%1];" : "=r"(v) : "r"(a)); return v; }
__device__ __forceinline__ uint2 lds64(uint32_t a) { uint2 v; asm volatile("ld.shared.v2.b32 {%0,%1}, [%2];" : "=r"(v.x), "=r"(v.y) : "r"(a)); return v; }
__device__ __forceinline__ uint4 lds128(uint32_t a) { uint4 v; asm volatile("ld.shared.v4.b32 {%0,%1,%2,%3}, [%4];" : "=r"(v.x), "=r"(v.y), "=r"(v.z), "=r"(v.w) : "r"(a)); return v; }
__device__ __forceinline__ float ldsf(uint32_t a) { return __uint_as_float(lds32(a)); }
__device__ __forceinline__ float2 ldsf2(uint32_t a) { uint2 v = lds64(a); return make_float2(__uint_as_float(v.x), __uint_as_float(v.y)); }
__device__ __forceinline__ void sts16(uint32_t a, uint32_t v) { asm volatile("st.shared.b16 [%0], %1;" ::"r"(a), "h"((unsigned short)v) : "memory"); }
__device__ __forceinline__ void sts32(uint32_t a, uint32_t v) { asm volatile("st.shared.b32 [%0], %1;" ::"r"(a), "r"(v) : "memory"); }
__device__ __forceinline__ void stsf(uint32_t a, float v) { sts32(a, __float_as_uint(v)); }
__device__ __forceinline__ void sts64(uint32_t a, uint32_t x, uint32_t y) { asm volatile("st.shared.v2.b32 [%0], {%1,%2};" ::"r"(a), "r"(x), "r"(y) : "memory"); }
__device__ __forceinline__ void sts128(uint32_t a, uint4 v) { asm volatile("st.shared.v4.b32 [%0], {%1,%2,%3,%4};" ::"r"(a), "r"(v.x), "r"(v.y), "r"(v.z), "r"(v.w) : "memory"); }
__device__ __forceinline__ void ldsm4(uint32_t* r, uint32_t a) { asm volatile("ldmatrix.sync.aligned.m8n8.x4.shared.b16 {%0,%1,%2,%3}, [%4];" : "=r"(r[0]), "=r"(r[1]), "=r"(r[2]), "=r"(r[3]) : "r"(a)); }
__device__ __forceinline__ void ldsm2t(uint32_t* r, uint32_t a) { asm volatile("ldmatrix.sync.aligned.m8n8.x2.trans.shared.b16 {%0,%1}, [%2];" : "=r"(r[0]), "=r"(r[1]) : "r"(a)); }
__device__ __forceinline__ void ldsm4t(uint32_t* r, uint32_t a) { asm volatile("ldmatrix.sync.aligned.m8n8.x4.trans.shared.b16 {%0,%1,%2,%3}, [%4];" : "=r"(r[0]), "=r"(r[1]), "=r"(r[2]), "=r"(r[3]) : "r"(a)); }
__device__ __forceinline__ void stsm4(uint32_t a, uint32_t r0, uint32_t r1, uint32_t r2, uint32_t r3) { asm volatile("stmatrix.sync.aligned.m8n8.x4.shared.b16 [%0], {%1,%2,%3,%4};" ::"r"(a), "r"(r0), "r"(r1), "r"(r2), "r"(r3) : "memory"); }

__device__ __forceinline__ uint32_t ldg16(const void* p) { uint32_t v; asm volatile("ld.global.nc.u16 %0, [%1];" : "=r"(v) : "l"(p)); return v; }
__device__ __forceinline__ uint32_t ldg32(const void* p) { uint32_t v; asm volatile("ld.global.nc.b32 %0, [%1];" : "=r"(v) : "l"(p)); return v; }
__device__ __forceinline__ uint4 ldg128(const void* p) { uint4 v; asm volatile("ld.global.nc.L1::no_allocate.v4.b32 {%0,%1,%2,%3}, [%4];" : "=r"(v.x), "=r"(v.y), "=r"(v.z), "=r"(v.w) : "l"(p)); return v; }
__device__ __forceinline__ uint32_t ldr32(const void* p) { uint32_t v; asm volatile("ld.relaxed.gpu.global.b32 %0, [%1];" : "=r"(v) : "l"(p) : "memory"); return v; }
__device__ __forceinline__ uint2 ldr64(const void* p) { uint2 v; asm volatile("{.reg .b64 t; ld.relaxed.gpu.global.b64 t, [%2]; mov.b64 {%0,%1}, t;}" : "=r"(v.x), "=r"(v.y) : "l"(p) : "memory"); return v; }
__device__ __forceinline__ uint4 ldr128(const void* p) { uint4 v; asm volatile("{.reg .b128 t; ld.relaxed.gpu.global.b128 t, [%4]; mov.b128 {%0,%1,%2,%3}, t;}" : "=r"(v.x), "=r"(v.y), "=r"(v.z), "=r"(v.w) : "l"(p) : "memory"); return v; }
__device__ __forceinline__ void str32(void* p, uint32_t v) { asm volatile("st.relaxed.gpu.global.b32 [%0], %1;" ::"l"(p), "r"(v) : "memory"); }
__device__ __forceinline__ void str64(void* p, uint32_t x, uint32_t y) { asm volatile("{.reg .b64 t; mov.b64 t, {%1,%2}; st.relaxed.gpu.global.b64 [%0], t;}" ::"l"(p), "r"(x), "r"(y) : "memory"); }
__device__ __forceinline__ void str128(void* p, uint4 v) { asm volatile("{.reg .b128 t; mov.b128 t, {%1,%2,%3,%4}; st.relaxed.gpu.global.b128 [%0], t;}" ::"l"(p), "r"(v.x), "r"(v.y), "r"(v.z), "r"(v.w) : "memory"); }
__device__ __forceinline__ void stg32(void* p, uint32_t v) { asm volatile("st.global.b32 [%0], %1;" ::"l"(p), "r"(v) : "memory"); }
__device__ __forceinline__ void stg128(void* p, uint32_t x, uint32_t y, uint32_t z, uint32_t w) { asm volatile("st.global.v4.b32 [%0], {%1,%2,%3,%4};" ::"l"(p), "r"(x), "r"(y), "r"(z), "r"(w) : "memory"); }
__device__ __forceinline__ uint32_t fbits(float f) { return __float_as_uint(f); }
__device__ __forceinline__ uint32_t tagw(uint32_t w, uint32_t ep) { uint32_t r; asm("lop3.b32 %0, %1, %2, 1, 0xD8;" : "=r"(r) : "r"(w), "r"(ep)); return r; }
__device__ __forceinline__ uint32_t tagf(float f, uint32_t ep) { return tagw(fbits(f), ep); }
__device__ __forceinline__ uint32_t stale(uint32_t bad, uint32_t w, uint32_t ep) { uint32_t r; asm("lop3.b32 %0, %1, %2, %3, 0xF6;" : "=r"(r) : "r"(bad), "r"(w), "r"(ep)); return r; }

__device__ __forceinline__ uint32_t pack2(float lo, float hi) { uint32_t r; asm("cvt.rn.bf16x2.f32 %0, %1, %2;" : "=r"(r) : "f"(hi), "f"(lo)); return r; }
__device__ __forceinline__ float blo(uint32_t v) { return __uint_as_float(v << 16); }
__device__ __forceinline__ float bhi(uint32_t v) { return __uint_as_float(v & 0xFFFF0000u); }
__device__ __forceinline__ float bround(float v) { return blo(pack2(v, 0.f)); }
__device__ __forceinline__ uint32_t hadd2(uint32_t a, uint32_t b) { uint32_t r; asm("add.rn.bf16x2 %0, %1, %2;" : "=r"(r) : "r"(a), "r"(b)); return r; }
__device__ __forceinline__ uint32_t hmul2(uint32_t a, uint32_t b) { uint32_t r; asm("mul.rn.bf16x2 %0, %1, %2;" : "=r"(r) : "r"(a), "r"(b)); return r; }
__device__ __forceinline__ uint32_t prmt(uint32_t a, uint32_t b, uint32_t s) { uint32_t r; asm("prmt.b32 %0, %1, %2, %3;" : "=r"(r) : "r"(a), "r"(b), "r"(s)); return r; }
__device__ __forceinline__ float rcp(float v) { float r; asm("rcp.approx.ftz.f32 %0, %1;" : "=f"(r) : "f"(v)); return r; }
__device__ __forceinline__ float rsq(float v) { float r; asm("rsqrt.approx.ftz.f32 %0, %1;" : "=f"(r) : "f"(v)); return r; }
__device__ __forceinline__ float shx(float v, int m) { return __shfl_xor_sync(0xffffffffu, v, m); }
__device__ __forceinline__ float gelu_t(float v, float k0, float k1) {
    float t;
    asm volatile("tanh.approx.f32 %0, %1;" : "=f"(t) : "f"(v * fmaf(v * v, k1, k0)));
    return t;
}
constexpr float GK0 = 0.7978845608028654f, GK1 = 0.0356774081363001f;
__device__ __forceinline__ uint32_t split2(float c) { const float h = bround(c); return pack2(c - h, h); }
template <int NV> __device__ __forceinline__ void halve(float* v, int mask, bool up) {
#pragma unroll
    for (int i = 0; i < NV / 2; i++) {
        float send = up ? v[i] : v[i + NV / 2], keep = up ? v[i + NV / 2] : v[i];
        v[i] = keep + shx(send, mask);
    }
}

struct cf { float x, y; };
__device__ __forceinline__ cf cmul(cf a, cf b) { cf r; r.x = fmaf(a.x, b.x, -a.y * b.y); r.y = fmaf(a.x, b.y, a.y * b.x); return r; }
__device__ __forceinline__ cf cexp2(float e, float th) {
    float m; asm("ex2.approx.ftz.f32 %0, %1;" : "=f"(m) : "f"(e));
    cf r; r.x = m * __cosf(th); r.y = m * __sinf(th); return r;
}

__device__ __forceinline__ void mma(float* d, uint32_t a0, uint32_t a1, uint32_t a2, uint32_t a3, uint32_t b0, uint32_t b1) {
    asm volatile("mma.sync.aligned.m16n8k16.row.col.f32.bf16.bf16.f32 {%0,%1,%2,%3},{%4,%5,%6,%7},{%8,%9},{%0,%1,%2,%3};"
                 : "+f"(d[0]), "+f"(d[1]), "+f"(d[2]), "+f"(d[3]) : "r"(a0), "r"(a1), "r"(a2), "r"(a3), "r"(b0), "r"(b1));
}
__device__ __forceinline__ void mmap(float* d, const uint32_t* a, const uint32_t* b) { mma(d, a[0], a[1], a[2], a[3], b[0], b[1]); }
__device__ __forceinline__ void mmar(float* d, const float* c, const uint32_t* a, const uint32_t* b) {
    asm volatile("mma.sync.aligned.m16n8k16.row.col.f32.bf16.bf16.f32 {%0,%1,%2,%3},{%4,%5,%6,%7},{%8,%9},{%10,%11,%12,%13};"
                 : "=f"(d[0]), "=f"(d[1]), "=f"(d[2]), "=f"(d[3])
                 : "r"(a[0]), "r"(a[1]), "r"(a[2]), "r"(a[3]), "r"(b[0]), "r"(b[1]), "f"(c[0]), "f"(c[1]), "f"(c[2]), "f"(c[3]));
}
__device__ __forceinline__ uint32_t cpy(uint32_t a, uint32_t z, int k) { return a + z * (uint32_t)k; }

#define WG_FENCE() asm volatile("wgmma.fence.sync.aligned;" ::: "memory")
#define WG_COMMIT() asm volatile("wgmma.commit_group.sync.aligned;" ::: "memory")
#define WG_WAIT(n) asm volatile("wgmma.wait_group.sync.aligned " #n ";" ::: "memory")
template <int N> __device__ __forceinline__ void pin(float* d) {
#pragma unroll
    for (int i = 0; i < N; i++) asm volatile("" : "+f"(d[i])::"memory");
}
template <int N> __device__ __forceinline__ void pinu(uint32_t* d) {
#pragma unroll
    for (int i = 0; i < N; i++) asm volatile("" : "+r"(d[i])::"memory");
}
constexpr uint32_t SMEM_BASE = 1024;
__device__ __forceinline__ uint32_t dlo(uint32_t off, uint32_t lbo) { return ((SMEM_BASE + off) >> 4) + ((lbo >> 4) << 16); }
template <int TA> __device__ __forceinline__ void wgmma_ss64(float* d, uint32_t da, uint32_t db, int sd) {
    asm volatile("{.reg .pred p; .reg .b64 a, b; setp.ne.b32 p, %34, 0; mov.b64 a, {%32, 0x40000040}; mov.b64 b, {%33, 0x40000040};\n"
                 "wgmma.mma_async.sync.aligned.m64n64k16.f32.bf16.bf16 {%0, %1, %2, %3, %4, %5, %6, %7, %8, %9, %10, %11, %12, %13, %14, %15, %16, %17, %18, %19, %20, %21, %22, %23, %24, %25, %26, %27, %28, %29, %30, %31}, a, b, p, 1, 1, %35, 1;}"
                 : "+f"(d[0]), "+f"(d[1]), "+f"(d[2]), "+f"(d[3]), "+f"(d[4]), "+f"(d[5]), "+f"(d[6]), "+f"(d[7]),
                   "+f"(d[8]), "+f"(d[9]), "+f"(d[10]), "+f"(d[11]), "+f"(d[12]), "+f"(d[13]), "+f"(d[14]), "+f"(d[15]),
                   "+f"(d[16]), "+f"(d[17]), "+f"(d[18]), "+f"(d[19]), "+f"(d[20]), "+f"(d[21]), "+f"(d[22]), "+f"(d[23]),
                   "+f"(d[24]), "+f"(d[25]), "+f"(d[26]), "+f"(d[27]), "+f"(d[28]), "+f"(d[29]), "+f"(d[30]), "+f"(d[31])
                 : "r"(da), "r"(db), "r"(sd), "n"(TA));
}
__device__ __forceinline__ void wgmma_ss224(float* d, uint32_t da, uint32_t db, int sd) {
    asm volatile("{.reg .pred p; .reg .b64 a, b; setp.ne.b32 p, %114, 0; mov.b64 a, {%112, 0x40000040}; mov.b64 b, {%113, 0x80000020};\n"
                 "wgmma.mma_async.sync.aligned.m64n224k16.f32.bf16.bf16 {%0, %1, %2, %3, %4, %5, %6, %7, %8, %9, %10, %11, %12, %13, %14, %15, %16, %17, %18, %19, %20, %21, %22, %23, %24, %25, %26, %27, %28, %29, %30, %31, %32, %33, %34, %35, %36, %37, %38, %39, %40, %41, %42, %43, %44, %45, %46, %47, %48, %49, %50, %51, %52, %53, %54, %55, %56, %57, %58, %59, %60, %61, %62, %63, %64, %65, %66, %67, %68, %69, %70, %71, %72, %73, %74, %75, %76, %77, %78, %79, %80, %81, %82, %83, %84, %85, %86, %87, %88, %89, %90, %91, %92, %93, %94, %95, %96, %97, %98, %99, %100, %101, %102, %103, %104, %105, %106, %107, %108, %109, %110, %111}, a, b, p, 1, 1, %115, 1;}"
                 : "+f"(d[0]), "+f"(d[1]), "+f"(d[2]), "+f"(d[3]), "+f"(d[4]), "+f"(d[5]), "+f"(d[6]), "+f"(d[7]),
                   "+f"(d[8]), "+f"(d[9]), "+f"(d[10]), "+f"(d[11]), "+f"(d[12]), "+f"(d[13]), "+f"(d[14]), "+f"(d[15]),
                   "+f"(d[16]), "+f"(d[17]), "+f"(d[18]), "+f"(d[19]), "+f"(d[20]), "+f"(d[21]), "+f"(d[22]), "+f"(d[23]),
                   "+f"(d[24]), "+f"(d[25]), "+f"(d[26]), "+f"(d[27]), "+f"(d[28]), "+f"(d[29]), "+f"(d[30]), "+f"(d[31]),
                   "+f"(d[32]), "+f"(d[33]), "+f"(d[34]), "+f"(d[35]), "+f"(d[36]), "+f"(d[37]), "+f"(d[38]), "+f"(d[39]),
                   "+f"(d[40]), "+f"(d[41]), "+f"(d[42]), "+f"(d[43]), "+f"(d[44]), "+f"(d[45]), "+f"(d[46]), "+f"(d[47]),
                   "+f"(d[48]), "+f"(d[49]), "+f"(d[50]), "+f"(d[51]), "+f"(d[52]), "+f"(d[53]), "+f"(d[54]), "+f"(d[55]),
                   "+f"(d[56]), "+f"(d[57]), "+f"(d[58]), "+f"(d[59]), "+f"(d[60]), "+f"(d[61]), "+f"(d[62]), "+f"(d[63]),
                   "+f"(d[64]), "+f"(d[65]), "+f"(d[66]), "+f"(d[67]), "+f"(d[68]), "+f"(d[69]), "+f"(d[70]), "+f"(d[71]),
                   "+f"(d[72]), "+f"(d[73]), "+f"(d[74]), "+f"(d[75]), "+f"(d[76]), "+f"(d[77]), "+f"(d[78]), "+f"(d[79]),
                   "+f"(d[80]), "+f"(d[81]), "+f"(d[82]), "+f"(d[83]), "+f"(d[84]), "+f"(d[85]), "+f"(d[86]), "+f"(d[87]),
                   "+f"(d[88]), "+f"(d[89]), "+f"(d[90]), "+f"(d[91]), "+f"(d[92]), "+f"(d[93]), "+f"(d[94]), "+f"(d[95]),
                   "+f"(d[96]), "+f"(d[97]), "+f"(d[98]), "+f"(d[99]), "+f"(d[100]), "+f"(d[101]), "+f"(d[102]), "+f"(d[103]),
                   "+f"(d[104]), "+f"(d[105]), "+f"(d[106]), "+f"(d[107]), "+f"(d[108]), "+f"(d[109]), "+f"(d[110]), "+f"(d[111])
                 : "r"(da), "r"(db), "r"(sd), "n"(0));
}
template <int TB> __device__ __forceinline__ void wgmma_rs64(float* d, uint32_t a0, uint32_t a1, uint32_t a2, uint32_t a3, uint32_t db, int sd) {
    asm volatile("{.reg .pred p; .reg .b64 b; setp.ne.b32 p, %37, 0; mov.b64 b, {%36, %39};\n"
                 "wgmma.mma_async.sync.aligned.m64n64k16.f32.bf16.bf16 {%0, %1, %2, %3, %4, %5, %6, %7, %8, %9, %10, %11, %12, %13, %14, %15, %16, %17, %18, %19, %20, %21, %22, %23, %24, %25, %26, %27, %28, %29, %30, %31}, {%32, %33, %34, %35}, b, p, 1, 1, %38;}"
                 : "+f"(d[0]), "+f"(d[1]), "+f"(d[2]), "+f"(d[3]), "+f"(d[4]), "+f"(d[5]), "+f"(d[6]), "+f"(d[7]),
                   "+f"(d[8]), "+f"(d[9]), "+f"(d[10]), "+f"(d[11]), "+f"(d[12]), "+f"(d[13]), "+f"(d[14]), "+f"(d[15]),
                   "+f"(d[16]), "+f"(d[17]), "+f"(d[18]), "+f"(d[19]), "+f"(d[20]), "+f"(d[21]), "+f"(d[22]), "+f"(d[23]),
                   "+f"(d[24]), "+f"(d[25]), "+f"(d[26]), "+f"(d[27]), "+f"(d[28]), "+f"(d[29]), "+f"(d[30]), "+f"(d[31])
                 : "r"(a0), "r"(a1), "r"(a2), "r"(a3), "r"(db), "r"(sd), "n"(TB), "n"(TB ? 0x40000040 : 8));
}
__device__ __forceinline__ void wgmma_rs224(float* d, uint32_t a0, uint32_t a1, uint32_t a2, uint32_t a3, uint32_t db, int sd) {
    asm volatile("{.reg .pred p; .reg .b64 b; setp.ne.b32 p, %117, 0; mov.b64 b, {%116, %119};\n"
                 "wgmma.mma_async.sync.aligned.m64n224k16.f32.bf16.bf16 {%0, %1, %2, %3, %4, %5, %6, %7, %8, %9, %10, %11, %12, %13, %14, %15, %16, %17, %18, %19, %20, %21, %22, %23, %24, %25, %26, %27, %28, %29, %30, %31, %32, %33, %34, %35, %36, %37, %38, %39, %40, %41, %42, %43, %44, %45, %46, %47, %48, %49, %50, %51, %52, %53, %54, %55, %56, %57, %58, %59, %60, %61, %62, %63, %64, %65, %66, %67, %68, %69, %70, %71, %72, %73, %74, %75, %76, %77, %78, %79, %80, %81, %82, %83, %84, %85, %86, %87, %88, %89, %90, %91, %92, %93, %94, %95, %96, %97, %98, %99, %100, %101, %102, %103, %104, %105, %106, %107, %108, %109, %110, %111}, {%112, %113, %114, %115}, b, p, 1, 1, %118;}"
                 : "+f"(d[0]), "+f"(d[1]), "+f"(d[2]), "+f"(d[3]), "+f"(d[4]), "+f"(d[5]), "+f"(d[6]), "+f"(d[7]),
                   "+f"(d[8]), "+f"(d[9]), "+f"(d[10]), "+f"(d[11]), "+f"(d[12]), "+f"(d[13]), "+f"(d[14]), "+f"(d[15]),
                   "+f"(d[16]), "+f"(d[17]), "+f"(d[18]), "+f"(d[19]), "+f"(d[20]), "+f"(d[21]), "+f"(d[22]), "+f"(d[23]),
                   "+f"(d[24]), "+f"(d[25]), "+f"(d[26]), "+f"(d[27]), "+f"(d[28]), "+f"(d[29]), "+f"(d[30]), "+f"(d[31]),
                   "+f"(d[32]), "+f"(d[33]), "+f"(d[34]), "+f"(d[35]), "+f"(d[36]), "+f"(d[37]), "+f"(d[38]), "+f"(d[39]),
                   "+f"(d[40]), "+f"(d[41]), "+f"(d[42]), "+f"(d[43]), "+f"(d[44]), "+f"(d[45]), "+f"(d[46]), "+f"(d[47]),
                   "+f"(d[48]), "+f"(d[49]), "+f"(d[50]), "+f"(d[51]), "+f"(d[52]), "+f"(d[53]), "+f"(d[54]), "+f"(d[55]),
                   "+f"(d[56]), "+f"(d[57]), "+f"(d[58]), "+f"(d[59]), "+f"(d[60]), "+f"(d[61]), "+f"(d[62]), "+f"(d[63]),
                   "+f"(d[64]), "+f"(d[65]), "+f"(d[66]), "+f"(d[67]), "+f"(d[68]), "+f"(d[69]), "+f"(d[70]), "+f"(d[71]),
                   "+f"(d[72]), "+f"(d[73]), "+f"(d[74]), "+f"(d[75]), "+f"(d[76]), "+f"(d[77]), "+f"(d[78]), "+f"(d[79]),
                   "+f"(d[80]), "+f"(d[81]), "+f"(d[82]), "+f"(d[83]), "+f"(d[84]), "+f"(d[85]), "+f"(d[86]), "+f"(d[87]),
                   "+f"(d[88]), "+f"(d[89]), "+f"(d[90]), "+f"(d[91]), "+f"(d[92]), "+f"(d[93]), "+f"(d[94]), "+f"(d[95]),
                   "+f"(d[96]), "+f"(d[97]), "+f"(d[98]), "+f"(d[99]), "+f"(d[100]), "+f"(d[101]), "+f"(d[102]), "+f"(d[103]),
                   "+f"(d[104]), "+f"(d[105]), "+f"(d[106]), "+f"(d[107]), "+f"(d[108]), "+f"(d[109]), "+f"(d[110]), "+f"(d[111])
                 : "r"(a0), "r"(a1), "r"(a2), "r"(a3), "r"(db), "r"(sd), "n"(0), "n"(0 ? 0x40000040 : 8));
}


__device__ __forceinline__ uint32_t vecpos(int kw) { return (kw >> 4) * 64 + (kw & 3) * 16 + ((kw >> 2) & 1) * 8 + ((kw >> 3) & 1) * 4; }

__device__ __forceinline__ uint32_t wstage(int q) { return (q & 1) * 28672 + (q & 2) * 32768; }

__global__ void __launch_bounds__(384, 1)
fused_kernel(const Params P, const __grid_constant__ Maps M)
{
    extern __shared__ __align__(1024) uint8_t smem_raw[];
    const uint32_t sb = __shfl_sync(0xffffffffu, (uint32_t)__cvta_generic_to_shared(smem_raw), 0);
    const int tid = threadIdx.x, lane = tid & 31, warp = __shfl_sync(0xffffffffu, tid >> 5, 0), g = lane >> 2, q = lane & 3;
    const int cl = blockIdx.x >> 1, pr = blockIdx.x & 1;
    int gi, pa;
    if (cl < 4) { gi = 15; pa = cl; } else if (cl < 36) { gi = (cl - 4) & 7; pa = (cl - 4) >> 3; } else { gi = 8 + (cl - 36) % 7; pa = (cl - 36) / 7; }
    const int fs = 2 * pa + pr;
    const int cs = 4 * pr + pa;
    const int b = 8 * gi + fs;
    const uint32_t bar0 = sb + SM_BAR;
#define BAR(i) (bar0 + 8 * (i))
#define G (*P.gs)

    if (warp < 8) {
        const int s = warp >> 2, w4 = warp & 3, wt = tid & 127;
        asm volatile("barrier.cluster.arrive.relaxed.aligned;" ::: "memory");
        const size_t po = (size_t)b * 512 + 2 * tid;
        const uint32_t ldt = ldg16(P.logdt + 4 * b + (warp >> 1));
        const uint32_t pAre = ldg32(P.Are + po), pAim = ldg32(P.Aim + po), pBre = ldg32(P.Bre + po), pBim = ldg32(P.Bim + po),
                       pCre = ldg32(P.Cre + po), pCim = ldg32(P.Cim + po);
        const uint32_t dsk = ldg16(P.dskip + 4 * b + (warp >> 1));
        uint32_t ep = ldr32(&G.epoch[b]);
        asm volatile("setmaxnreg.inc.sync.aligned.u32 224;");
#pragma unroll
        for (int i = 0; i < 3; i++) sts128(sb + SM_WD + (tid + 256 * i) * 16, make_uint4(0, 0, 0, 0));
        if (tid < 168) sts128(tid < 8 ? sb + SM_WD + (768 + tid) * 16 : sb + SM_UW + ((tid - 8) / 40) * UW_B + ((tid - 8) % 40) * 16, make_uint4(0, 0, 0, 0));
        {
            const int mh = warp & 1;
            uint32_t sa_[3][2];
            {
                const uint32_t wd = sb + SM_WD + (warp >> 1) * WD_B + (16 * mh + g) * 4, sel = 0x4410u + 0x22u * (q & 1);
#define CBW(a, c) ((uint32_t)(4 * (a)) | ((uint32_t)(4 * (c)) << 16))
#define CBS(a, c, d, e) (wd + prmt(q & 2 ? CBW(d, e) : CBW(a, c), 0u, sel))
                sa_[0][0] = CBS(T0o, T2o, T4o, TM2o + 1); sa_[0][1] = CBS(T1o, T3o, T5o, TM1o + 1);
                sa_[1][0] = CBS(T0o + 32, T4o + 32, T0o + 64, T0o + 96); sa_[1][1] = CBS(T2o + 32, TM2o + 33, T4o + 64, T4o + 96);
                sa_[2][0] = wd + 4 * (T0o + 128) + 256 * q; sa_[2][1] = sa_[2][0] + 128;
#undef CBW
#undef CBS
                pinu<6>(&sa_[0][0]);
            }
            const uint32_t pt = sb + SM_W1 + warp * PT_B;
            {
                const float dt = bround(expf(blo(ldt)));
                cf z[2], w[2], r0[2], r2[2], r4[2], t[2];
#pragma unroll
                for (int m = 0; m < 2; m++) {
                    const float a = dt * (m ? bhi(pAre) : blo(pAre)) * 1.4426950408889634f, th = dt * (m ? bhi(pAim) : blo(pAim));
                    const cf z64 = cexp2(64.f * a, 64.f * th);
                    sts128(pt + 24 * PT_PITCH + lane * 32 + m * 16, make_uint4(__float_as_uint(8.f * a), __float_as_uint(8.f * th), __float_as_uint(z64.x), __float_as_uint(z64.y)));
                    z[m] = cexp2(a, -th); w[m] = cexp2(256.f * a, -256.f * th);
                    cf C, B;
                    C.x = m ? bhi(pCre) : blo(pCre); C.y = -(m ? bhi(pCim) : blo(pCim));
                    B.x = dt * (m ? bhi(pBre) : blo(pBre)); B.y = -dt * (m ? bhi(pBim) : blo(pBim));
                    r0[m] = cmul(C, B);
                }
                const uint32_t pp = pt + lane * 8;
#define PST(j, v) sts64(pp + (j) * PT_PITCH, pack2(v[0].x, v[0].y), pack2(v[1].x, v[1].y))
#define CM(d, a, c) d[0] = cmul(a[0], c[0]); d[1] = cmul(a[1], c[1])
                PST(0, r0); CM(t, r0, z); PST(1, t); CM(r2, t, z); PST(2, r2); CM(t, r2, z); PST(3, t); CM(r4, t, z); PST(4, r4);
                CM(r2, r2, w); PST(9, r2); CM(t, r4, z); PST(5, t); CM(r2, t, z); PST(6, r2); CM(t, r2, z); PST(7, t); CM(r2, r2, w); PST(11, r2);
                CM(r0, r0, w); PST(8, r0); CM(r4, r4, w); PST(10, r4); CM(r0, r0, w); PST(12, r0); CM(r4, r4, w); PST(13, r4);
                CM(r0, r0, w); PST(14, r0); CM(r4, r4, w); PST(15, r4);
#pragma unroll 1
                for (int j = 16; j < 21; j++) { CM(r0, r0, w); PST(j, r0); }
#undef PST
#undef CM
            }
            __syncwarp();
            float KA[2][3][4];
#pragma unroll
            for (int n = 0; n < 24; n++) (&KA[0][0][0])[n] = 0.f;
            const uint32_t ba = pt + (lane & 7) * PT_PITCH + (lane >> 3) * 16, pa_ = pt + 24 * PT_PITCH + q * 16;
            const float gf = (float)g;
            uint4 pv[2]; cf en[2];
#pragma unroll
            for (int m = 0; m < 2; m++) { pv[m] = lds128(pa_ + m * 64); en[m] = cexp2(gf * __uint_as_float(pv[m].x), gf * __uint_as_float(pv[m].y)); }
#pragma unroll 1
            for (int k = 0; k < 4; k++) {
                uint32_t bb[3][4];
                uint4 pn[2][2];
#pragma unroll
                for (int i = 0; i < 4; i++) pn[i >> 1][i & 1] = lds128(pa_ + k * 256 + 128 + i * 64);
#pragma unroll
                for (int n = 0; n < 3; n++) ldsm4(bb[n], ba + n * 8 * PT_PITCH + k * 64);
#pragma unroll
                for (int h = 0; h < 2; h++) {
                    uint32_t a[2][4];
#pragma unroll
                    for (int m = 0; m < 2; m++) {
                        cf e = en[m], z64;
                        z64.x = __uint_as_float(pv[m].z); z64.y = __uint_as_float(pv[m].w);
                        pv[m] = pn[h][m];
                        en[m] = cexp2(gf * __uint_as_float(pv[m].x), gf * __uint_as_float(pv[m].y));
                        a[0][2 * m] = pack2(e.x, e.y); e = cmul(e, z64); a[0][2 * m + 1] = pack2(e.x, e.y); e = cmul(e, z64);
                        a[1][2 * m] = pack2(e.x, e.y); e = cmul(e, z64); a[1][2 * m + 1] = pack2(e.x, e.y);
                    }
#pragma unroll
                    for (int n = 0; n < 3; n++) { mmap(KA[0][n], a[0], bb[n] + 2 * h); mmap(KA[1][n], a[1], bb[n] + 2 * h); }
                }
            }
            float KG[3][4];
#pragma unroll
            for (int n = 0; n < 3; n++) {
                sts128(sb + SM_XS + warp * 1536 + n * 512 + lane * 16, mh ? make_uint4(__float_as_uint(KA[0][n][0]), __float_as_uint(KA[0][n][1]), __float_as_uint(KA[0][n][2]), __float_as_uint(KA[0][n][3]))
                                                    : make_uint4(__float_as_uint(KA[1][n][0]), __float_as_uint(KA[1][n][1]), __float_as_uint(KA[1][n][2]), __float_as_uint(KA[1][n][3])));
            }
            bar_sync(5, 384);
            if (tid == 0) {
                fence_async_smem(); fence_async_global();
                asm volatile("cp.async.bulk.shared::cluster.global.mbarrier::complete_tx::bytes [%0], [%1], 16384, [%2];" ::"r"(sb + SM_ST), "l"(G.stats0), "r"(BAR(B_ST)) : "memory");
            }
#pragma unroll
            for (int n = 0; n < 3; n++) {
                const uint4 v = lds128(sb + SM_XS + (warp ^ 1) * 1536 + n * 512 + lane * 16);
                KG[n][0] = __uint_as_float(v.x) + (mh ? KA[1][n][0] : KA[0][n][0]); KG[n][1] = __uint_as_float(v.y) + (mh ? KA[1][n][1] : KA[0][n][1]);
                KG[n][2] = __uint_as_float(v.z) + (mh ? KA[1][n][2] : KA[0][n][2]); KG[n][3] = __uint_as_float(v.w) + (mh ? KA[1][n][3] : KA[0][n][3]);
            }
            if (mh == 0 && lane == 0) KG[0][0] += blo(dsk);
#pragma unroll
            for (int n = 0; n < 3; n++)
#pragma unroll
                for (int e = 0; e < 2; e++) {
                    const uint32_t a = sa_[n][e], v = pack2(KG[n][e], KG[n][2 + e]);
                    const bool ok0 = n < 2 || q < 2 || (e == 0 && q == 2 && mh == 0), ok1 = n < 2 || q < 2;
                    if (ok0) { sts16(a, v); sts16(a + 6, v); }
                    if (ok1) { sts16(a + 32, v >> 16); sts16(a + 38, v >> 16); }
                }
        }
        ep += 1;
        bar_sync(1, 256);
        {
            const int o = g - 2 * q;
            const uint32_t wd = sb + SM_WD + w4 * WD_B + 4 * o;
            const uint32_t sel0 = (o >= 0 ? 0x54u : 0x10u) | (o >= 1 ? 0x7600u : 0x3200u);
            const uint32_t oz = lds32(sb + SM_WD);
            uint32_t ub = sb + SM_UW + w4 * UW_B + 160 * q + 8 * g;
            uint32_t dep = sb + SM_DEP + w4 * 512 + lane * 16;
            const float zero4[4] = {0.f, 0.f, 0.f, 0.f};
            uint32_t A[32][4], f[9][2];
#define LT(T, h) lds32(wd + 4 * ((T) + 8 * (h)))
#define QUAD(Q, a0, a1, a2, a3, id) { Q[0] = a0; Q[1] = a1; Q[2] = cpy(a2, oz, 2 * (id) + 3); Q[3] = cpy(a3, oz, 2 * (id) + 4); }
#define QF(Q, X, L, id) QUAD(Q, X[2 * (L)], X[2 * (L) + 1], (L) ? X[(L) ? 2 * (L) - 1 : 0] : 0u, X[2 * (L)], id)
#define AN(e, L) A[3 * (e) + (L)]
#define AM(e, L) A[24 + 2 * (e) + (L) - 3]
#define A0(a) A[a]
#define A4(a) A[11 + (a)]
#define LF(k) { const uint2 v_ = lds64(ub + (8 - (k)) * 8); f[k][0] = v_.x; f[k][1] = v_.y; }
#define SUM3(d, a, c, e) { d[0] = hadd2(hadd2(f[a][0], f[c][0]), f[e][0]); d[1] = hadd2(hadd2(f[a][1], f[c][1]), f[e][1]); }
#define SUMX(d, p, a, c) { d[0] = hadd2(p[0], hadd2(f[a][0], f[c][0])); d[1] = hadd2(p[1], hadd2(f[a][1], f[c][1])); }
            if (s) {
                {
                    const uint32_t sel1 = (o >= 1 ? 0x54u : 0x10u) | (o >= 2 ? 0x7600u : 0x3200u);
                    uint32_t T0[10], T4[10], X[10];
#pragma unroll
                    for (int h = 0; h < 10; h++) { T0[h] = LT(T0o, h); T4[h] = LT(T4o, h); }
#pragma unroll
                    for (int L = 0; L < 3; L++) { QF(AN(2, L), T0, L, 0) QF(AN(6, L), T4, L, 1) }
#pragma unroll
                    for (int L = 3; L < 5; L++) { QF(AM(1, L), T0, L, 0) QF(AM(3, L), T4, L, 1) }
#pragma unroll
                    for (int k = 0; k < 2; k++) {
#pragma unroll
                        for (int h = 0; h < 9; h++) X[h] = LT(k ? T2o : TM2o, h);
                        X[8] = prmt(X[8], T0[8], k ? sel0 : sel1); X[9] = cpy(T0[9], oz, 31 + k);
#pragma unroll
                        for (int L = 0; L < 3; L++) QF(AN(4 * k, L), X, L, 2 + k)
#pragma unroll
                        for (int L = 3; L < 5; L++) QF(AM(2 * k, L), X, L, 2 + k)
                    }
#pragma unroll
                    for (int k = 0; k < 4; k++) {
#pragma unroll
                        for (int h = 0; h < 5; h++) X[h] = LT(k == 0 ? TM1o : k == 1 ? T1o : k == 2 ? T3o : T5o, h);
                        X[4] = prmt(X[4], k < 2 ? T0[4] : T4[4], k ? sel0 : sel1); X[5] = cpy(k < 2 ? T0[5] : T4[5], oz, 33 + k);
#pragma unroll
                        for (int L = 0; L < 3; L++) QF(AN(2 * k + 1, L), X, L, 4 + k)
                    }
                }
                float Pa[5][4], Ra[3][4];
                uint32_t u3[2];
                mbar_wait(BAR(B_UB));
                LF(1) LF(2)
                mmar(Pa[1], zero4, AN(0, 1), f[1]); mmar(Pa[2], zero4, AN(0, 2), f[1]);
                mmar(Pa[3], zero4, AM(0, 3), f[1]); mmar(Pa[4], zero4, AM(0, 4), f[1]);
                mmar(Ra[1], zero4, AN(1, 1), f[2]); mmar(Ra[2], zero4, AN(1, 2), f[2]);
                mmap(Pa[3], AM(1, 3), f[2]); mmap(Pa[4], AM(1, 4), f[2]);
                ub += 640;
                LF(1) LF(2) LF(3) LF(4) LF(5) LF(6) LF(7) LF(8)
#pragma unroll 1
                for (int lim = 15; lim >= 2; lim--) {
                    ub += 640;
                    if (lim == 8) mbar_wait(BAR(B_UB + 1));
                    SUM3(u3, 2, 4, 3)
                    mmar(Pa[0], Pa[1], AN(0, 0), f[1]); mmar(Pa[1], Pa[2], AN(0, 1), f[1]); mmar(Pa[2], Pa[3], AN(0, 2), f[1]);
                    mmar(Pa[3], Pa[4], AM(0, 3), f[1]); mmar(Pa[4], zero4, AM(0, 4), f[1]); LF(1)
                    mmar(Ra[0], Ra[1], AN(1, 0), f[2]); mmar(Ra[1], Ra[2], AN(1, 1), f[2]); mmar(Ra[2], zero4, AN(1, 2), f[2]); LF(2)
                    mmap(Pa[0], AN(2, 0), f[3]); mmap(Pa[1], AN(2, 1), f[3]); mmap(Pa[2], AN(2, 2), f[3]); LF(3)
                    mmap(Pa[3], AM(1, 3), u3); mmap(Pa[4], AM(1, 4), u3);
                    SUM3(u3, 6, 8, 7)
                    mmap(Ra[0], AN(3, 0), f[4]); mmap(Ra[1], AN(3, 1), f[4]); mmap(Ra[2], AN(3, 2), f[4]); LF(4)
                    mmap(Pa[0], AN(4, 0), f[5]); mmap(Pa[1], AN(4, 1), f[5]); mmap(Pa[2], AN(4, 2), f[5]);
                    mmap(Ra[0], AN(5, 0), f[6]);
                    mmap(Pa[3], AM(2, 3), f[5]); mmap(Pa[4], AM(2, 4), f[5]); LF(5)
                    mmap(Pa[0], AN(6, 0), f[7]); mmap(Ra[1], AN(5, 1), f[6]);
                    mmap(Ra[0], AN(7, 0), f[8]); mmap(Ra[2], AN(5, 2), f[6]); LF(6)
                    mmap(Pa[1], AN(6, 1), f[7]); mmap(Pa[2], AN(6, 2), f[7]); LF(7)
                    mmap(Pa[3], AM(3, 3), u3); mmap(Pa[4], AM(3, 4), u3);
                    mmap(Ra[1], AN(7, 1), f[8]); mmap(Ra[2], AN(7, 2), f[8]); LF(8)
                    sts128(dep, make_uint4(__float_as_uint(Pa[0][0] + Ra[0][0]), __float_as_uint(Pa[0][1] + Ra[0][1]),
                                           __float_as_uint(Pa[0][2] + Ra[0][2]), __float_as_uint(Pa[0][3] + Ra[0][3])));
                    dep += 2048;
                    warp_arrive(BAR(B_NEAR + 15 - lim));
                }
#pragma unroll 1
                for (int lim = 1; lim >= 0; lim--) {
                    ub += 640;
                    mmar(Pa[0], Pa[1], AN(0, 0), f[1]); mmar(Ra[0], Ra[1], AN(1, 0), f[2]); mmar(Pa[1], Pa[2], AN(0, 1), f[1]); mmar(Ra[1], Ra[2], AN(1, 1), f[2]); LF(1) LF(2)
                    mmap(Pa[0], AN(2, 0), f[3]); mmap(Ra[0], AN(3, 0), f[4]); mmap(Pa[1], AN(2, 1), f[3]); mmap(Ra[1], AN(3, 1), f[4]); LF(3) LF(4)
                    mmap(Pa[0], AN(4, 0), f[5]); mmap(Ra[0], AN(5, 0), f[6]); mmap(Pa[1], AN(4, 1), f[5]); mmap(Ra[1], AN(5, 1), f[6]); LF(5) LF(6)
                    mmap(Pa[0], AN(6, 0), f[7]); mmap(Ra[0], AN(7, 0), f[8]); mmap(Pa[1], AN(6, 1), f[7]); mmap(Ra[1], AN(7, 1), f[8]); LF(7) LF(8)
                    sts128(dep, make_uint4(__float_as_uint(Pa[0][0] + Ra[0][0]), __float_as_uint(Pa[0][1] + Ra[0][1]),
                                           __float_as_uint(Pa[0][2] + Ra[0][2]), __float_as_uint(Pa[0][3] + Ra[0][3])));
                    dep += 2048;
                    warp_arrive(BAR(B_NEAR + 15 - lim));
                }
                mbar_wait(BAR(B_W1RDY));
#pragma unroll 1
                for (int k = wt; k < 512; k += 128) {
                    const uint32_t c1 = lds32(sb + SM_CBV + vecpos(k >> 1)), c2 = prmt(c1, c1, (k & 1) ? 0x3232u : 0x1010u), ra = sb + SM_W1 + k * 128;
#pragma unroll 1
                    for (int h = 0; h < 8; h += 4) {
                        uint4 w[4];
#pragma unroll
                        for (int j = 0; j < 4; j++) w[j] = lds128(ra + (((h + j) ^ (k & 7)) << 4));
#pragma unroll
                        for (int j = 0; j < 4; j++) sts128(ra + (((h + j) ^ (k & 7)) << 4), make_uint4(hmul2(w[j].x, c2), hmul2(w[j].y, c2), hmul2(w[j].z, c2), hmul2(w[j].w, c2)));
                    }
                }
                fence_async_smem();
                warp_arrive(BAR(B_W1SC));
            } else {
                {
                    const int rho = wt & 7, hh = (wt >> 3) & 1;
                    mbar_wait(BAR(B_MOD));
                    const uint4 sa4 = lds128(sb + SM_OWN), ca4 = lds128(sb + SM_OWN + 16);
                    const float sa[4] = {__uint_as_float(sa4.x), __uint_as_float(sa4.y), __uint_as_float(sa4.z), __uint_as_float(sa4.w)};
                    const float ca[4] = {__uint_as_float(ca4.x), __uint_as_float(ca4.y), __uint_as_float(ca4.z), __uint_as_float(ca4.w)};
                    mbar_wait(BAR(B_ST));
#pragma unroll 1
                    for (int blk = wt >> 4; blk < 16; blk += 8) {
                        const int t0 = 128 * blk + 32 * hh + rho - 5, e0 = t0 < 0 ? 8 : 0, e9 = t0 >= 2048 - 96 ? 88 : 96;
#define ROW(i) ((i) == 0 ? e0 : (i) == 9 ? e9 : ((i) / 5) * 64 + ((i) % 5) * 8)
                        uint2 st[10];
                        uint32_t bad = 0;
#pragma unroll
                        for (int i = 0; i < 10; i++) { st[i] = lds64(sb + SM_ST + (t0 + ROW(i)) * 8); bad = stale(bad, st[i].x, ep); }
                        for (int it = 0; any(bad); it++) {
                            bad = 0;
#pragma unroll
                            for (int i = 0; i < 10; i++) { st[i] = ldr64(&G.stats0[t0 + ROW(i)]); bad = stale(bad, st[i].x, ep); }
                            if (it > SPIN_MAX) __trap();
                        }
                        mbar_wait(BAR(B_XC + (blk >> 3)));
                        const uint32_t uw = sb + SM_UW + (blk + 1) * 640 + hh * 320 + rho * 8, xs = sb + SM_XC + t0 * 16 + 8 * pr;
                        const uint32_t xb = sb + SM_XS + 4 * (160 * blk + 40 * hh + rho - 5);
                        float hp[2][4];
#pragma unroll
                        for (int i = 0; i < 5; i++) {
                            float h[2][4];
#pragma unroll
                            for (int u = 0; u < 2; u++) {
                                const uint2 xc = lds64(xs + 1024 * u + 128 * i);
                                const float r = __uint_as_float(st[5 * u + i].x), c = __uint_as_float(st[5 * u + i].y);
                                h[u][0] = fmaf(fmaf(blo(xc.x), r, c), ca[0], sa[0]); h[u][1] = fmaf(fmaf(bhi(xc.x), r, c), ca[1], sa[1]);
                                h[u][2] = fmaf(fmaf(blo(xc.y), r, c), ca[2], sa[2]); h[u][3] = fmaf(fmaf(bhi(xc.y), r, c), ca[3], sa[3]);
                                if ((u == 0 && i == 0 && e0) || (u == 1 && i == 4 && e9 == 88)) h[u][0] = h[u][1] = h[u][2] = h[u][3] = 0.f;
                                const uint32_t xd = xb + 320 * u + 32 * i + (i == 4 && rho >= 5 ? 32 : 0);
                                if (i || (u == 0 && (unsigned)t0 < 3u)) { sts32(xd, xc.x); sts32(xd + XS_B, xc.y); }
                            }
#pragma unroll
                            for (int c = 0; c < 4; c++) {
                                if (i) sts64(uw + c * UW_B + 160 * ((i - 1) >> 1) + 64 * ((i - 1) & 1), pack2(hp[0][c], h[0][c]), pack2(hp[1][c], h[1][c]));
                                else if ((unsigned)t0 < 3u) sts32(uw + c * UW_B - 92, pack2(0.f, h[0][c]));
                                hp[0][c] = h[0][c]; hp[1][c] = h[1][c];
                            }
                        }
#undef ROW
                        warp_arrive(BAR(B_UB + (blk >> 3)));
                    }
                }
                {
                    const uint32_t selp = (g & 1) ? 0x7610u : 0x1010u;
                    uint32_t T0[33], T4[32];
#pragma unroll
                    for (int h = 9; h < 33; h++) T0[h] = LT(T0o, h);
#pragma unroll
                    for (int h = 9; h < 17; h++) T4[h] = LT(T4o, h);
                    const uint32_t T3x = prmt(T4[16], T0[16], sel0), T5x = prmt(T4[16], LT(T0o + 1, 16), sel0), T5y = LT(T0o + 1, 17);
                    QUAD(A[22], T3x, cpy(T0[17], oz, 31), T4[15], T3x, 2)
                    QUAD(A[23], q ? T5x : (T5x & 0xFFFF0000u), q ? T5y : (T5y & 0xFFFF0000u), T4[15], T5x, 3)
#pragma unroll
                    for (int h = 16; h < 32; h++) {
                        const uint32_t v = prmt(lds32(wd + 4 * (g & 1) + 4 * (T0o + 8 * h)), T0[h], selp);
                        T4[h] = h == 16 ? prmt(T4[16], v, sel0) : v;
                    }
                    QUAD(A[24], 0u, 0u, T0[31], q == 3 ? (T0[32] & 0xFFFF0000u) : 0u, 4)
#pragma unroll
                    for (int L = 5; L < 16; L++) { QF(A0(L - 5), T0, L, 0) QF(A4(L - 5), T4, L, 1) }
                }
                float Fa[12][4], Fx[4];
                uint32_t u3[2], u5[2], u7[2];
                mbar_wait(BAR(B_UB)); mbar_wait(BAR(B_UB + 1));
                LF(0) LF(1) LF(2)
                u5[0] = hadd2(f[1][0], f[2][0]); u5[1] = hadd2(f[1][1], f[2][1]); u7[0] = hadd2(u5[0], f[0][0]); u7[1] = hadd2(u5[1], f[0][1]);
#pragma unroll
                for (int a = 0; a < 11; a++) mmar(Fa[a], zero4, A0(a), a < 4 ? u5 : u7);
                mmar(Fa[11], zero4, A[24], u7);
                ub += 640;
                LF(0) LF(1) LF(2) LF(3) LF(4) LF(5) LF(6) LF(7) LF(8)
                uint32_t xa = sb + SM_XS + (w4 >> 1) * XS_B + 4 * (8 * g + 2 * q + 8 * (g >> 2)), nb = BAR(B_NEAR);
                bf16* xo = G.x2t + (size_t)(4 * b + w4) * 2048 + 8 * g + 2 * q;
                const uint32_t xsel = (w4 & 1) ? 0x3244u : 0x1044u;
                mbar_wait(BAR(B_MOD + 1));
                const float ga = ldsf(sb + SM_OWN + 32 + 4 * w4);
#define FARLOOP(NA) _Pragma("unroll 1") for (int i = 0; i < 4; i++) { \
                    const uint2 x0 = lds64(xa), x1 = lds64(xa + 320); \
                    mbar_wait(nb); \
                    const uint4 nv = lds128(dep); \
                    float ov[4] = {__uint_as_float(prmt(x0.x, 0, xsel)), __uint_as_float(prmt(x0.y, 0, xsel)), __uint_as_float(prmt(x1.x, 0, xsel)), __uint_as_float(prmt(x1.y, 0, xsel))}; \
                    if (NA) { ov[0] = fmaf(ga, Fa[0][0], ov[0]); ov[1] = fmaf(ga, Fa[0][1], ov[1]); ov[2] = fmaf(ga, Fa[0][2], ov[2]); ov[3] = fmaf(ga, Fa[0][3], ov[3]); } \
                    stg32(xo, pack2(fmaf(ga, __uint_as_float(nv.x), ov[0]), fmaf(ga, __uint_as_float(nv.y), ov[1]))); \
                    stg32(xo + 64, pack2(fmaf(ga, __uint_as_float(nv.z), ov[2]), fmaf(ga, __uint_as_float(nv.w), ov[3]))); \
                    if (NA == 7 || NA == 3) { __syncwarp(); if (lane == 0 && i == (NA == 7 ? 0 : 3)) mbar_arrive(BAR(B_CONV + (NA == 3))); } \
                    xa += 640; xo += 128; dep += 2048; nb += 8; \
                    if (NA) { \
                        ub += 640; \
                        SUM3(u3, 6, 8, 7) SUM3(u5, 2, 4, 3) SUMX(u5, u5, 1, 5) \
                        if (NA > 3) { SUMX(u7, u5, 0, 6) LF(0) } \
                        LF(1) LF(2) LF(3) LF(4) LF(5) \
                        mmar(Fa[0], Fa[1], A4(0), u3); mmar(Fa[1], Fa[2], A4(1), u3); mmar(Fa[2], Fa[3], A4(2), u3); \
                        if (NA > 3) { \
                            mmar(Fa[3], Fa[4], A[22], f[6]); mmar(Fx, zero4, A[23], f[8]); \
                            _Pragma("unroll") for (int a = 4; a < NA; a++) mmar(Fa[a], Fa[a + 1], A4(a), f[7]); \
                            mmap(Fa[3], A4(3), f[7]); mmap(Fx, A0(3), u5); \
                        } \
                        LF(6) LF(7) LF(8) \
                        mmap(Fa[0], A0(0), u5); mmap(Fa[1], A0(1), u5); mmap(Fa[2], A0(2), u5); \
                        if (NA > 3) { \
                            _Pragma("unroll") for (int a = 4; a < NA; a++) mmap(Fa[a], A0(a), u7); \
                            Fa[3][0] += Fx[0]; Fa[3][1] += Fx[1]; Fa[3][2] += Fx[2]; Fa[3][3] += Fx[3]; \
                        } \
                    } }
                FARLOOP(0) FARLOOP(11)
                FARLOOP(7) FARLOOP(3)
#undef FARLOOP
            }
#undef LT
#undef QUAD
#undef QF
#undef LF
#undef SUM3
#undef SUMX
#undef AN
#undef AM
#undef A0
#undef A4
        }

        const int tau = 16 * s + gi, row0 = 64 * tau + 16 * w4 + g;
        float acc[32];
        uint32_t x2p[16];
        {
            float dx[4] = {0.f, 0.f, 0.f, 0.f}, dy[4] = {0.f, 0.f, 0.f, 0.f};
            const uint32_t soff = (32 * (w4 >> 1) + 8 * (w4 & 1) + 16 * ((lane >> 3) & 1) + (lane & 7)) * 128 + ((cs ^ (lane & 7)) << 4);
            const uint32_t xoff = (8 * (lane >> 4) + (lane & 7)) * 128 + (((2 * w4 + ((lane >> 3) & 1)) ^ (lane & 7)) << 4);
            uint32_t ca_ = sb + SM_CBV + 64 * (w4 >> 1) + 8 * (w4 & 1) + 16 * q, va = g < 2 ? ca_ + 1024 * g : sb + SM_ONE;
            mbar_wait(BAR(B_W1SC));
            int slot = (8 * s) % NSLOT;
#pragma unroll 1
            for (int c = 0; c < 8; c++) {
                const uint32_t ta = sb + SM_Q + slot * 8192;
                const uint2 cv = lds64(ca_), vv = lds64(va);
                ca_ += 128; va += g < 2 ? 128 : 0;
                mbar_wait(BAR(B_FULL + 8 * s + c));
                uint32_t xv[2];
                ldsm2t(xv, ta + soff);
                const uint32_t da = dlo(SM_Q + slot * 8192, 8192), db = dlo(SM_W1 + c * 8192, 8192);
                WG_FENCE();
#pragma unroll
                for (int k = 0; k < 4; k++) wgmma_ss64<1>(acc, da + 128 * k, db + 128 * k, (c | k) != 0);
                WG_COMMIT();
                const uint32_t y0 = hmul2(xv[0], cv.x), y1 = hmul2(xv[1], cv.y);
                mma(dx, xv[0], vv.x, xv[1], vv.y, xv[0], xv[1]);
                mma(dy, y0, vv.x, y1, vv.y, y0, y1);
                slot = slot == NSLOT - 1 ? 0 : slot + 1;
            }
            const uint32_t red = sb + SM_RED + s * 768;
            if (g < 4) { const uint32_t a = red + g * 128 + q * 32 + w4 * 4; stsf(a, g == 3 ? dx[2] : dy[2]); stsf(a + 16, g == 3 ? dx[3] : dy[3]); }
            if (q == (g >> 1)) { const uint32_t a = red + 512 + g * 16 + w4 * 4; stsf(a, (g & 1) ? dx[1] : dx[0]); stsf(a + 128, (g & 1) ? dy[1] : dy[0]); }
            bar_sync(2 + s, 128);
            if (wt < 8) {
                float S[6];
#pragma unroll
                for (int k = 0; k < 6; k++) {
                    const uint4 v = lds128(red + 128 * k + 16 * wt);
                    S[k] = (__uint_as_float(v.x) + __uint_as_float(v.y)) + (__uint_as_float(v.z) + __uint_as_float(v.w));
                }
                const uint4 k4 = lds128(sb + SM_CONST);
                const float Cc = __uint_as_float(k4.x), Cs = __uint_as_float(k4.y), Ccc = __uint_as_float(k4.z), Ccs = __uint_as_float(k4.w), Css = ldsf(sb + SM_CONST + 16);
                const float n1 = 1.f / 512.f;
                const float m1 = S[3] * n1, r1 = rsq(fmaxf(fmaf(-m1, m1, S[4] * n1), 0.f) + LN_EPS);
                const float m2 = fmaf(r1, fmaf(-m1, Cc, S[2]), Cs) * n1;
                const float e2 = (r1 * r1 * (S[5] - 2.f * m1 * S[0] + m1 * m1 * Ccc) + 2.f * r1 * fmaf(-m1, Ccs, S[1]) + Css) * n1;
                const float r2 = rsq(fmaxf(fmaf(-m2, m2, e2), 0.f) + LN_EPS), s1 = rcp(r1);
                str128(&G.stats1[64 * tau + 8 * cs + wt], make_uint4(split2(-m1), split2(s1), split2(-m2 * s1), tagf(r1 * r2, ep)));
            }
            __syncwarp();
#pragma unroll
            for (int n = 0; n < 4; n++) ldsm4t(x2p + 4 * n, sb + SM_Q + ((8 * s + cs) % NSLOT) * 8192 + xoff + n * 2048);
            mbar_wait(BAR(B_U));
            uint4 s0 = ldr128(&G.stats1[row0]), s1 = ldr128(&G.stats1[row0 + 8]);
            WG_WAIT(0);
            warp_arrive(BAR(B_TILE + s));
            while (any(stale(s0.w ^ ep, s1.w, ep))) { s0 = ldr128(&G.stats1[row0]); s1 = ldr128(&G.stats1[row0 + 8]); }
            {
                const uint32_t a0 = q == 0 ? s0.x : q == 1 ? s0.y : q == 2 ? s0.z : 0u, a1 = q == 0 ? s1.x : q == 1 ? s1.y : q == 2 ? s1.z : 0u;
                WG_FENCE();
                wgmma_rs64<0>(acc, a0, a1, a0, a1, dlo(SM_U123, 1024), 1);
                WG_COMMIT();
            }
            const float al[2] = {__uint_as_float(s0.w), __uint_as_float(s1.w)};
            const float k0[2] = {GK0 * al[0], GK0 * al[1]}, k1[2] = {GK1 * al[0] * al[0] * al[0], GK1 * al[1] * al[1] * al[1]}, kh[2] = {0.5f * al[0], 0.5f * al[1]};
            WG_WAIT(0);
            pin<32>(acc);
            uint32_t gp[2][8];
#pragma unroll
            for (int r = 0; r < 2; r++)
#pragma unroll
                for (int n = 0; n < 8; n++) {
                    const float v0 = acc[4 * n + 2 * r], v1 = acc[4 * n + 2 * r + 1], h0 = kh[r] * v0, h1 = kh[r] * v1;
                    gp[r][n] = pack2(fmaf(h0, gelu_t(v0, k0[r], k1[r]), h0), fmaf(h1, gelu_t(v1, k0[r], k1[r]), h1));
                }
            bf16* go = G.g + (size_t)row0 * 512 + 64 * cs + 8 * q;
#pragma unroll
            for (int r = 0; r < 2; r++) {
                stg128(go + r * 4096, gp[r][0], gp[r][1], gp[r][2], gp[r][3]);
                stg128(go + r * 4096 + 32, gp[r][4], gp[r][5], gp[r][6], gp[r][7]);
            }
            bar_sync(2 + s, 128);
            if (wt == 0) asm volatile("st.release.gpu.global.b32 [%0], %1;" ::"l"(&G.flag[(tau * 8 + cs) * 32]), "r"(ep) : "memory");
            const float r1[2] = {rcp(blo(s0.y) + bhi(s0.y)), rcp(blo(s1.y) + bhi(s1.y))};
            const float c1[2] = {(blo(s0.x) + bhi(s0.x)) * r1[0], (blo(s1.x) + bhi(s1.x)) * r1[1]};
#pragma unroll
            for (int n = 0; n < 8; n++) {
                const uint32_t a = sb + SM_CBV + 128 * cs + 16 * q + vecpos(4 * n), cv = lds32(a), sv = lds32(a + 1024);
#pragma unroll
                for (int r = 0; r < 2; r++) {
                    acc[4 * n + 2 * r] = fmaf(fmaf(blo(x2p[2 * n + r]), r1[r], c1[r]), blo(cv), blo(sv));
                    acc[4 * n + 2 * r + 1] = fmaf(fmaf(bhi(x2p[2 * n + r]), r1[r], c1[r]), bhi(cv), bhi(sv));
                }
            }
        }
        {
            mbar_wait(BAR(B_W2FULL));
            int slot = (16 + 8 * s) % NSLOT;
#pragma unroll 1
            for (int c = 0; c < 8; c++) {
                mbar_wait(BAR(B_FULL + 16 + 8 * s + c));
                const uint32_t da = dlo(SM_Q + slot * 8192, 16), db = dlo(SM_W2 + c * 8192, 8192);
                WG_FENCE();
#pragma unroll
                for (int k = 0; k < 4; k++) wgmma_ss64<0>(acc, da + 2 * k, db + 128 * k, 1);
                WG_COMMIT();
                slot = slot == NSLOT - 1 ? 0 : slot + 1;
            }
            WG_WAIT(0);
            pin<32>(acc);
            warp_arrive(BAR(B_TILE + 2 + s));
            bf16* xo = G.x1 + (size_t)row0 * 512 + 64 * cs + 8 * q;
            float sm[2] = {0.f, 0.f}, sq[2] = {0.f, 0.f};
#pragma unroll
            for (int r = 0; r < 2; r++)
#pragma unroll
                for (int h = 0; h < 2; h++) {
                    const float* a = acc + 16 * h + 2 * r;
                    stg128(xo + r * 4096 + 32 * h, pack2(a[0], a[1]), pack2(a[4], a[5]), pack2(a[8], a[9]), pack2(a[12], a[13]));
                }
#pragma unroll
            for (int i = 0; i < 32; i++) { sm[(i >> 1) & 1] += acc[i]; sq[(i >> 1) & 1] = fmaf(acc[i], acc[i], sq[(i >> 1) & 1]); }
#pragma unroll
            for (int r = 0; r < 2; r++) { sm[r] += shx(sm[r], 1); sq[r] += shx(sq[r], 1); sm[r] += shx(sm[r], 2); sq[r] += shx(sq[r], 2); }
            if (q < 2) G.stats2[2048 * cs + row0 + 8 * q] = q ? make_float2(sm[1], sq[1]) : make_float2(sm[0], sq[0]);
            bar_sync(2 + s, 128);
            if (wt == 0) asm volatile("st.release.gpu.global.b32 [%0], %1;" ::"l"(&G.flag[((32 + tau) * 8 + cs) * 32]), "r"(ep) : "memory");
#pragma unroll
            for (int n = 0; n < 8; n++) {
                const float2 gv = ldsf2(sb + SM_GB + (8 * n + 2 * q) * 4);
#pragma unroll
                for (int r = 0; r < 2; r++) {
                    acc[4 * n + 2 * r] = fmaf(gv.x, acc[4 * n + 2 * r], blo(x2p[2 * n + r]));
                    acc[4 * n + 2 * r + 1] = fmaf(gv.y, acc[4 * n + 2 * r + 1], bhi(x2p[2 * n + r]));
                }
            }
        }
        uint32_t H[56];
        float hr[2];
        const uint32_t hbuf = sb + SM_H + (s ? 0 : 28672) + wt * 16, rb0 = mapa(bar0, pr ^ 1);
        {
            float e[112];
            mbar_wait(BAR(B_SEEN + s));
            const float2* sp = G.stats2 + 4096 * q + row0;
            const uint2 p0 = ldr64(sp), p1 = ldr64(sp + 8), p2 = ldr64(sp + 2048), p3 = ldr64(sp + 2056);
            int slot = (32 + 8 * s) % NSLOT;
#pragma unroll 1
            for (int c = 0; c < 8; c++) {
                mbar_wait(BAR(B_FULL + 32 + 8 * s + c));
                mbar_wait(BAR(B_WFULL + c));
                const uint32_t da = dlo(SM_Q + slot * 8192, 16), db = dlo(wstage(c), 2048);
                WG_FENCE();
#pragma unroll
                for (int k = 0; k < 4; k++) wgmma_ss224(e, da + 2 * k, db + 64 * (k & 1) + 896 * (k >> 1), (c | k) != 0);
                WG_COMMIT();
                if (c) {
                    WG_WAIT(1); __syncwarp();
                    if (lane == 0) {
                        mbar_arrive(BAR(B_WEMPTY + c - 1));
                        if (!s) mbar_arrive(BAR(B_EMPTY + c - 1));
                        else if (c == 4) mbar_arrive_remote(rb0 + 8 * B_HFREE);
                    }
                }
                slot = slot == NSLOT - 1 ? 0 : slot + 1;
            }
            float sm[2] = {__uint_as_float(p0.x) + __uint_as_float(p2.x), __uint_as_float(p1.x) + __uint_as_float(p3.x)};
            float sq[2] = {__uint_as_float(p0.y) + __uint_as_float(p2.y), __uint_as_float(p1.y) + __uint_as_float(p3.y)};
            float k0[2], k1[2];
            uint32_t am[2];
#pragma unroll
            for (int r = 0; r < 2; r++) {
                sm[r] += shx(sm[r], 1); sq[r] += shx(sq[r], 1); sm[r] += shx(sm[r], 2); sq[r] += shx(sq[r], 2);
                const float m = sm[r] * (1.f / 512.f), r3 = rsq(fmaxf(fmaf(-m, m, sq[r] * (1.f / 512.f)), 0.f) + LN_EPS);
                k0[r] = GK0 * r3; k1[r] = GK1 * r3 * r3 * r3; hr[r] = 0.5f * r3;
                am[r] = q < 2 ? split2(-m) : 0u;
            }
            mbar_wait(BAR(B_U + 1));
            WG_FENCE();
            wgmma_rs224(e, am[0], am[1], 0u, 0u, dlo(SM_U4, 0), 1);
            WG_COMMIT();
            WG_WAIT(0);
            pin<112>(e);
            __syncwarp();
            if (lane == 0) { mbar_arrive(BAR(B_WEMPTY + 7)); if (!s) mbar_arrive_remote(rb0 + 8 * (B_HFREE + 1)); }
            mbar_wait_cluster(BAR(B_HFREE + s));
#define SENDH(j) asm volatile("st.async.weak.shared::cluster.mbarrier::complete_tx::bytes.v4.b32 [%0], {%1,%2,%3,%4}, [%5];" \
            ::"r"(hbuf + (rb0 - bar0) + (j) * 2048), "r"(H[4 * (j)]), "r"(H[4 * (j) + 1]), "r"(H[4 * (j) + 2]), "r"(H[4 * (j) + 3]), "r"(rb0 + 8 * (B_HFULL + s)) : "memory")
#pragma unroll
            for (int k = 0; k < 14; k++) {
#pragma unroll
                for (int i = 0; i < 4; i++) {
                    const float v0 = e[8 * k + 2 * i], v1 = e[8 * k + 2 * i + 1];
                    H[4 * k + i] = pack2(fmaf(v0, gelu_t(v0, k0[i & 1], k1[i & 1]), v0), fmaf(v1, gelu_t(v1, k0[i & 1], k1[i & 1]), v1));
                }
                if (k % 3) SENDH(k - 1 - k / 3);
            }
        }
        {
            float X[32], Y[32];
            uint32_t Hp[56];
            uint4* pdst = G.part + (size_t)((gi * 8 + 4 * pr) * 6 + s) * 512 + wt;
#define TILE(D, A, j, first) { mbar_wait(BAR(B_WFULL + 8 + (j))); WG_FENCE(); \
            _Pragma("unroll") for (int k = 0; k < 14; k++) wgmma_rs64<1>(D, A[4 * k], A[4 * k + 1], A[4 * k + 2], A[4 * k + 3], dlo(wstage(j), 8192) + 128 * k, !(first) || k != 0); \
            WG_COMMIT(); if ((j) && (j) != 5) WG_WAIT(1); if ((j) && (j) < 5) warp_arrive(BAR(B_WEMPTY + 7 + (j))); }
#define SEND(D, st_) { pin<32>(D); uint4* pd = pdst + (((pa + (st_)) & 3) * 6 + 2 * ((st_) - 1)) * 512; \
            _Pragma("unroll") for (int v = 0; v < 4; v++) str128(pd + 128 * v, make_uint4(tagw(pack2(D[8 * v], D[8 * v + 1]), ep), pack2(D[8 * v + 2], D[8 * v + 3]), \
                                                                 pack2(D[8 * v + 4], D[8 * v + 5]), pack2(D[8 * v + 6], D[8 * v + 7]))); }
            pinu<56>(H);
            TILE(X, H, 0, true)
            SENDH(9); SENDH(10); SENDH(11); SENDH(12); SENDH(13);
            TILE(Y, H, 1, true)
            mbar_wait_cluster(BAR(B_HFULL + s));
#pragma unroll
            for (int k = 0; k < 14; k++) {
                const uint4 v = lds128(hbuf + k * 2048); Hp[4 * k] = v.x; Hp[4 * k + 1] = v.y; Hp[4 * k + 2] = v.z; Hp[4 * k + 3] = v.w;
                if (k < 8) sts128(hbuf + k * 2048, make_uint4(__float_as_uint(acc[4 * k]), __float_as_uint(acc[4 * k + 1]), __float_as_uint(acc[4 * k + 2]), __float_as_uint(acc[4 * k + 3])));
            }
            pinu<56>(Hp);
            TILE(X, Hp, 2, false)
            TILE(Y, Hp, 3, false)
            SEND(X, 1)
            TILE(X, H, 4, true)
            SEND(Y, 2)
            TILE(X, Hp, 5, false)
            TILE(Y, H, 6, true)
            SEND(X, 3)
            TILE(Y, Hp, 7, false)
            const uint4* psrc = pdst + pa * 6 * 512;
            uint4 pv[12];
            uint32_t bad;
            do {
                bad = 0;
#pragma unroll
                for (int i = 0; i < 12; i++) pv[i] = ldr128(psrc + (i >> 2) * 1024 + (i & 3) * 128);
#pragma unroll
                for (int i = 0; i < 12; i++) bad = stale(bad, pv[i].x, ep);
            } while (any(bad));
#pragma unroll
            for (int v = 0; v < 4; v++) {
                const uint32_t a[4] = {pv[v].x, pv[v].y, pv[v].z, pv[v].w}, c[4] = {pv[4 + v].x, pv[4 + v].y, pv[4 + v].z, pv[4 + v].w},
                               d[4] = {pv[8 + v].x, pv[8 + v].y, pv[8 + v].z, pv[8 + v].w};
#pragma unroll
                for (int i = 0; i < 4; i++) {
                    const float2 gv = ldsf2(sb + SM_GB + (16 * v + 8 * (i >> 1) + 2 * q) * 4);
                    const int j = 8 * v + 2 * i;
                    if (!(i & 1)) {
                        const uint4 t = lds128(hbuf + (2 * v + (i >> 1)) * 2048);
                        acc[j] = __uint_as_float(t.x); acc[j + 1] = __uint_as_float(t.y); acc[j + 2] = __uint_as_float(t.z); acc[j + 3] = __uint_as_float(t.w);
                    }
                    X[j] = gv.x * hr[i & 1]; X[j + 1] = gv.y * hr[i & 1];
                    acc[j] = fmaf(X[j], blo(a[i]) + blo(c[i]) + blo(d[i]), acc[j]);
                    acc[j + 1] = fmaf(X[j + 1], bhi(a[i]) + bhi(c[i]) + bhi(d[i]), acc[j + 1]);
                }
            }
            WG_WAIT(0);
            pin<32>(Y);
            const uint32_t stg = sb + SM_Q + warp * 2048;
            const int srow = (lane & 7) + 8 * ((lane >> 3) & 1);
#pragma unroll
            for (int n2 = 0; n2 < 4; n2++) {
                uint32_t o[4];
#pragma unroll
                for (int i = 0; i < 4; i++) { const int j = 8 * n2 + 2 * i; o[i] = pack2(fmaf(X[j], Y[j], acc[j]), fmaf(X[j + 1], Y[j + 1], acc[j + 1])); }
                stsm4(stg + srow * 128 + (((2 * n2 + (lane >> 4)) ^ (lane & 7)) << 4), o[0], o[1], o[2], o[3]);
            }
            __syncwarp();
            bf16* oo = P.out + (size_t)(64 * tau + 16 * w4 + (lane >> 3)) * 512 + 64 * cs + 8 * (lane & 7);
#pragma unroll
            for (int i = 0; i < 4; i++) {
                const int r = 4 * i + (lane >> 3);
                const uint4 v = lds128(stg + r * 128 + (((lane & 7) ^ (r & 7)) << 4));
                stg128(oo + i * 2048, v.x, v.y, v.z, v.w);
            }
            if (tid == 128) str32(&G.epoch[b], ep);
            warp_arrive(BAR(B_DONE));
#undef TILE
#undef SEND
#undef SENDH
        }
    } else {
        const int at = tid - 256, aw = warp - 8;
        if (aw) asm volatile("barrier.cluster.arrive.relaxed.aligned;" ::: "memory");
        asm volatile("setmaxnreg.dec.sync.aligned.u32 56;");
        uint4 xr[2][4];
        {
            const bf16* p = P.x + (size_t)(16 * b + g) * 512 + 128 * aw + 8 * q;
#pragma unroll
            for (int i = 0; i < 4; i++) { xr[0][i] = ldg128(p + 32 * i); xr[1][i] = ldg128(p + 4096 + 32 * i); }
        }
        const uint32_t cw = ldg32(P.c + 64 * (b & 7) + 2 * lane);
        uint32_t ep = ldr32(&G.epoch[b]);
        const int mcol = 64 * ((b >> 3) & 7) + 512 * (b >> 6);
        if (aw == 0) {
            if (lane == 0) {
#pragma unroll
                for (int i = 0; i <= B_AUXQ; i++) mbar_init(BAR(i), 1);
#pragma unroll
                for (int i = 0; i < B_AUXQ; i++) mbar_expect(BAR(i), i == B_XC ? 24576 : i == B_ST ? 16384 : 8192);
                asm volatile("fence.mbarrier_init.release.cluster;" ::: "memory");
            }
            __syncwarp();
            asm volatile("barrier.cluster.arrive.relaxed.aligned;" ::: "memory");
            if (lane == 0) tma2d(sb + SM_WM, &M.m[tmWm], mcol, 64 * (b & 7), BAR(B_WM));
            asm volatile("barrier.cluster.wait.aligned;" ::: "memory");
            if (lane == 0) {
#pragma unroll 1
                for (int i = 0; i < 4; i++) {
                    tma2d_pair(sb + SM_XC + (2 * i + pr) * 4096, &M.m[tmXc], 8 * (b >> 1), 256 * (2 * i + pr), BAR(B_XC + (i == 3)));
                    if (i == 1 || i == 2) tma2d(sb + SM_WM + 8192 * i, &M.m[tmWm], mcol + 512 * (b >> 6) + 512 + 512 * i, 64 * (b & 7), BAR(B_WM + i));
                }
            }
        } else {
            if (lane == 0) {
                uint32_t b0 = BAR(aw == 1 ? B_FULL : aw == 2 ? B_WFULL : B_NEAR);
                const uint32_t b1 = b0 + (aw == 2 ? 320 : 384);
                do {
#pragma unroll
                    for (int k = 0; k < 8; k++) mbar_init(b0 + 8 * k, aw == 3 ? 4 : 1);
                    b0 += 64;
                } while (b0 != b1);
                if (aw == 2) {
#pragma unroll
                    for (int i = B_WEMPTY; i <= B_DONE; i++) mbar_init(BAR(i), 8);
                    sts128(sb + SM_ONE, make_uint4(0x3F803F80u, 0x3F803F80u, 0x3F803F80u, 0x3F803F80u));
                }
                asm volatile("fence.mbarrier_init.release.cluster;" ::: "memory");
            }
            __syncwarp();
            if (aw == 1) { mbar_expect(BAR(B_FULL + lane), 8192); if (lane < 16) mbar_expect(BAR(B_FULL + 32 + lane), 8192); }
            if (aw == 2 && lane < 21) mbar_expect(BAR(B_WFULL + lane), lane < 18 ? 28672 : lane < 20 ? 65536 : 16384);
        }
        asm volatile("bar.arrive 5, 384;" ::: "memory");
        {
            const float c0 = blo(cw), c1 = bhi(cw);
            sts32(sb + SM_SCV + aw * 128 + vecpos(lane), pack2(__fdividef(c0, 1.f + __expf(-c0)), __fdividef(c1, 1.f + __expf(-c1))));
        }
        {
            float ds[4] = {0.f, 0.f, 0.f, 0.f}, d0[4] = {0.f, 0.f, 0.f, 0.f}, d1[4] = {0.f, 0.f, 0.f, 0.f};
#pragma unroll
            for (int i = 0; i < 4; i++) {
                const uint4 R = xr[0][i], S = xr[1][i];
                mma(ds, R.x, S.x, R.y, S.y, 0x3F803F80u, 0x3F803F80u); mma(d0, R.x, S.x, R.y, S.y, R.x, R.y); mma(d1, R.x, S.x, R.y, S.y, S.x, S.y);
                mma(ds, R.z, S.z, R.w, S.w, 0x3F803F80u, 0x3F803F80u); mma(d0, R.z, S.z, R.w, S.w, R.z, R.w); mma(d1, R.z, S.z, R.w, S.w, S.z, S.w);
            }
            if (q == (g >> 1)) {
                const uint32_t a = sb + SM_ARED + aw * 128 + g * 8;
                sts64(a, __float_as_uint(ds[0]), __float_as_uint((g & 1) ? d0[1] : d0[0]));
                sts64(a + 64, __float_as_uint(ds[2]), __float_as_uint((g & 1) ? d1[3] : d1[2]));
            }
            ep += 1;
            bar_sync(4, 128);
            if (aw == 3 && lane < 16) {
                const uint32_t a = sb + SM_ARED + lane * 8;
                const float2 v0 = ldsf2(a), v1 = ldsf2(a + 128), v2 = ldsf2(a + 256), v3 = ldsf2(a + 384);
                const float m = ((v0.x + v1.x) + (v2.x + v3.x)) * (1.f / 512.f), e2 = ((v0.y + v1.y) + (v2.y + v3.y)) * (1.f / 512.f);
                const float r = rsq(fmaxf(fmaf(-m, m, e2), 0.f) + LN_EPS);
                str64(&G.stats0[16 * b + lane], tagf(r, ep), fbits(-m * r));
            }
        }
        if (aw < 3) {
            const uint4 a0 = lds128(sb + SM_SCV + aw * 128 + q * 16), a1 = lds128(sb + SM_SCV + aw * 128 + 64 + q * 16);
            const uint32_t ta = sb + SM_WM + aw * 8192 + lane * 128;
            const int col = mcol + (aw ? 512 * (b >> 6) + 512 + 512 * aw : 0);
            float t0 = 0.f, t1 = 0.f;
            mbar_wait_b(BAR(B_WM + aw));
#pragma unroll 2
            for (int n = 0; n < 8; n++) {
                uint32_t b0[4], b1[4];
                ldsm4t(b0, ta + ((n ^ (lane & 7)) << 4)); ldsm4t(b1, ta + 4096 + ((n ^ (lane & 7)) << 4));
                float du[4] = {0.f, 0.f, 0.f, 0.f}, dl[4] = {0.f, 0.f, 0.f, 0.f};
                mma(du, a0.x, a0.y, a0.z, a0.w, b0[0], b0[1]); mma(dl, a0.x, a0.y, a0.z, a0.w, b0[2], b0[3]);
                mma(du, a1.x, a1.y, a1.z, a1.w, b1[0], b1[1]); mma(dl, a1.x, a1.y, a1.z, a1.w, b1[2], b1[3]);
                if (n == g) { t0 = du[0] + dl[2]; t1 = du[1] + dl[3]; }
            }
            str64(&G.modq[3072 * (b & 7) + col + 2 * lane], tagf(t0, ep), fbits(t1));
            if (at == 0) {
                mbar_wait_b(BAR(B_UB + 1)); mbar_wait(BAR(B_MOD + 1));
                fence_async_smem();
                tma2d(sb + SM_W1, &M.m[tmW1], 64 * cs, 0, BAR(B_W1FULL));
                tma2d(sb + SM_W1 + 32768, &M.m[tmW1], 64 * cs, 256, BAR(B_W1FULL));
            }
            if (at == 64) {
#pragma unroll 1
                for (int i = 0; i < tmCount; i++) asm volatile("prefetch.tensormap [%0];" ::"l"(&M.m[i]) : "memory");
            }
            if (aw == 1 && lane < 16) str128(&G.stats1[1024 * (lane >> 3) + 64 * gi + 8 * cs + (lane & 7)], make_uint4(ep + 1, ep + 1, ep + 1, ep + 1));
        } else {
#pragma unroll 1
            for (int rd = 0; rd < 2; rd++) {
                const int v = rd ? 2 + (lane >> 3) : (lane >> 3) & 1;
                uint4 w; int it = 0;
                do { w = ldr128(&G.modq[3072 * (lane & 7) + 512 * v + 4 * b]); if (++it > SPIN_MAX) __trap(); } while (any(stale(w.x ^ ep, w.z, ep)));
                float t[4] = {__uint_as_float(w.x), __uint_as_float(w.y), __uint_as_float(w.z), __uint_as_float(w.w)};
                const float one = (v == 1 || v == 4) ? 1.f : 0.f;
#pragma unroll
                for (int i = 0; i < 4; i++) {
                    t[i] += shx(t[i], 1); t[i] += shx(t[i], 2); t[i] += shx(t[i], 4);
                    t[i] = bround(one + bround(t[i]));
                }
                if (!(lane & 7)) {
                    if (v < 3) sts128(sb + SM_OWN + 16 * v, make_uint4(__float_as_uint(t[0]), __float_as_uint(t[1]), __float_as_uint(t[2]), __float_as_uint(t[3])));
                    if (rd) str128(&G.modp[4 * b + v - 2], make_uint4(tagf(t[0], ep), fbits(t[1]), fbits(t[2]), fbits(t[3])));
                }
                warp_arrive(BAR(B_MOD + rd));
            }
            if (lane == 0 && b < 112) { tma2d(sb + SM_W3C, &M.m[tmW3c], 16 * b, 0, BAR(B_W3C)); tma2d(sb + SM_W3C + 8192, &M.m[tmW3c], 16 * b, 256, BAR(B_W3C)); }
        }
        __syncwarp();
        {
            uint4 vs, vc, vg; int it = 0;
            do {
                vs = ldr128(&G.modp[4 * at + 1]); vc = ldr128(&G.modp[4 * at + 2]); vg = ldr128(&G.modp[4 * at + 3]);
                if (++it > SPIN_MAX) __trap();
            } while (any(stale(stale(vs.x ^ ep, vc.x, ep), vg.x, ep)));
            if (at == 32) { l2_prefetch(P.w2 + (size_t)b * 2048, 4096); l2_prefetch(P.w4 + (size_t)b * 7168, 14336); }
            const uint32_t vp = sb + SM_CBV + vecpos(2 * at);
            sts32(vp, prmt(vc.x, vc.y, 0x7632u)); sts32(vp + 16, prmt(vc.z, vc.w, 0x7632u));
            sts32(vp + 1024, prmt(vs.x, vs.y, 0x7632u)); sts32(vp + 1040, prmt(vs.z, vs.w, 0x7632u));
            if ((at >> 4) == cs) sts128(sb + SM_GB + (at & 15) * 16, make_uint4(vg.x & ~1u, vg.y, vg.z, vg.w));
            const float sv[4] = {bhi(vs.x), __uint_as_float(vs.y), __uint_as_float(vs.z), __uint_as_float(vs.w)};
            const float cv[4] = {bhi(vc.x), __uint_as_float(vc.y), __uint_as_float(vc.z), __uint_as_float(vc.w)};
            float v[8] = {0.f, 0.f, 0.f, 0.f, 0.f, 0.f, 0.f, 0.f};
#pragma unroll
            for (int i = 0; i < 4; i++) {
                v[0] += cv[i]; v[1] += sv[i]; v[2] = fmaf(cv[i], cv[i], v[2]); v[3] = fmaf(cv[i], sv[i], v[3]); v[4] = fmaf(sv[i], sv[i], v[4]);
            }
            halve<8>(v, 16, lane & 16); halve<4>(v, 8, lane & 8); halve<2>(v, 4, lane & 4);
            v[0] += shx(v[0], 2); v[0] += shx(v[0], 1);
            stsf(sb + SM_ARED + 512 + aw * 32 + g * 4, v[0]);
            bar_sync(4, 128);
            if (at < 5) { const uint32_t a = sb + SM_ARED + 512 + at * 4; stsf(sb + SM_CONST + 4 * at, (ldsf(a) + ldsf(a + 32)) + (ldsf(a + 64) + ldsf(a + 96))); }
            if (aw != 2) warp_arrive(BAR(B_W1RDY));
        }
        if (aw >= 2) {
            const bool uw = aw == 2;
            if (uw || b < 112) mbar_wait_b(BAR(uw ? B_W1FULL : B_W3C));
#pragma unroll 1
            for (int rd = uw ? (gi < 8) : 2 * (b < 112); rd > 0; rd--) {
                uint32_t ba = uw ? sb + SM_W1 + lane * 128 + ((gi ^ (lane & 7)) << 4) : sb + SM_W3C + lane * 32 + (rd - 1) * 16;
                uint32_t aa = uw && g < 2 ? sb + SM_CBV + g * 1024 + q * 16 : sb + SM_ONE;
                const uint32_t bstep = uw ? 4096 : 1024, astep = uw && g < 2 ? 64 : 0;
                float du[4] = {0.f, 0.f, 0.f, 0.f}, dl[4] = {0.f, 0.f, 0.f, 0.f};
#pragma unroll 2
                for (int i = 0; i < 16; i++) {
                    uint32_t bb[4];
                    ldsm4t(bb, ba); const uint4 a = lds128(aa);
                    mma(du, a.x, a.y, a.z, a.w, bb[0], bb[1]); mma(dl, a.x, a.y, a.z, a.w, bb[2], bb[3]);
                    ba += bstep; aa += astep;
                }
                if (g < (uw ? 3 : 1)) str64(uw ? &G.u123[512 * g + 64 * cs + 8 * gi + 2 * q] : &G.u4[16 * b + 8 * (rd - 1) + 2 * q], tagf(du[0] + dl[2], ep), tagf(du[1] + dl[3], ep));
            }
            warp_arrive(BAR(uw ? B_W1RDY : B_AUXQ));
        }
        if (aw < 2) {
            const int s = aw, tau = 16 * s + gi, c = lane & 7;
            const int sh = (c & 4 ? 2 : 1) * (c & 2 ? 1 : -1);
            mbar_wait(BAR(B_CONV + s));
            if (lane == 0) asm volatile("red.release.gpu.global.add.u32 [%0], 1;" ::"l"(&G.cnt[(8 * s + (b >> 4)) * 32]) : "memory");
            __syncwarp();
            mbar_wait(BAR(B_AUXQ));
#pragma unroll 1
            for (int ph = 0; ph < 3; ph++) {
                const uint32_t* fp; uint32_t target = ep; bool need = lane < 8;
                if (ph == 0) { fp = &G.cnt[((tau < 18 ? 0 : 8) + c) * 32]; target = 16 * ep; }
                else if (ph == 1) {
                    const int tn = lane < 8 ? tau : tau + (sh > 0 ? 1 : -1);
                    need = lane < 16 && tn >= 0 && tn < 32;
                    fp = &G.flag[((need ? tn : tau) * 8 + c) * 32];
                } else fp = &G.flag[((32 + tau) * 8 + c) * 32];
                const CUtensorMap* tm = &M.m[tmX2 + ph];
                const int n = 16 * ph + 8 * s + c;
                const uint32_t dst = sb + SM_Q + (n % NSLOT) * 8192;
                const int c0 = ph == 0 ? 64 * tau : 64 * c, c1 = ph == 0 ? 64 * c : 64 * tau + (ph == 1 ? sh : 0);
                const uint32_t eb = BAR(n < 32 + NSLOT ? B_TILE + ((n - NSLOT) >> 3) : B_EMPTY + n - 32 - NSLOT);
                bool pend = lane < 8, room = n < NSLOT, seen = ph != 2;
                for (;;) {
                    if (need) need = (int)(ldr32(fp) - target) < 0;
                    if (pend && !room) room = mbar_test(eb);
                    uint32_t m = __ballot_sync(0xffffffffu, need);
                    if (pend && room && !((m >> c) & 0x101)) {
                        fence_acquire(); fence_async_global();
                        tma2d(dst, tm, c0, c1, BAR(B_FULL + n));
                        pend = false;
                    }
                    if (!m && !seen) { fence_acquire(); warp_arrive(BAR(B_SEEN + s)); seen = true; }
                    if (!__any_sync(0xffffffffu, pend)) break;
                    if (!m) __nanosleep(40);
                }
            }
        } else if (aw == 2) {
            {
                uint2 v[3];
                do {
#pragma unroll
                    for (int k = 0; k < 3; k++) v[k] = ldr64(&G.u123[512 * k + 64 * cs + 2 * lane]);
                } while (any(stale(stale(v[0].x ^ ep, v[1].x, ep), v[2].x, ep)));
#pragma unroll
                for (int h = 0; h < 2; h++) {
                    const uint32_t w0 = split2(__uint_as_float(h ? v[0].y : v[0].x)), w1 = split2(__uint_as_float(h ? v[1].y : v[1].x)), w2 = split2(__uint_as_float(h ? v[2].y : v[2].x));
                    const uint32_t a = sb + SM_U123 + 32 * lane + 16 * h;
                    sts128(a, make_uint4(prmt(w0, w0, 0x3232u), prmt(w1, w1, 0x3232u), prmt(w2, w2, 0x3232u), 0u));
                    sts128(a + 1024, make_uint4(prmt(w0, w0, 0x1010u), prmt(w1, w1, 0x1010u), prmt(w2, w2, 0x1010u), 0u));
                }
                fence_async_smem();
                warp_arrive(BAR(B_U));
            }
            if (lane == 0) {
                mbar_wait(BAR(B_CONV + 1));
                fence_async_smem();
                tma5d(sb + SM_W2, &M.m[tmW2], 64 * cs, 0, 0, 0, 0, BAR(B_W2FULL));
#pragma unroll 1
                for (int t = 0; t < 8; t++) {
                    if (t < 4) { mbar_wait(BAR(B_TILE + (t & 2))); mbar_wait(BAR(B_TILE + (t | 1))); } else mbar_wait(BAR(B_WEMPTY + t - 4));
                    tma5d(sb + wstage(t), &M.m[tmW3], 0, 0, 8 * t, 0, 7 * fs, BAR(B_WFULL + t));
                    tma5d(sb + wstage(t) + 14336, &M.m[tmW3], 0, 0, 8 * t + 4, 0, 7 * fs, BAR(B_WFULL + t));
                }
#pragma unroll 1
                for (int j = 0; j < 8; j++) {
                    const int jj = (j == 1 || j == 2) ? 3 - j : j;
                    const int c0 = 64 * (4 * pr + ((pa + (jj >> 1) + 1) & 3)), c1 = 224 * (fs ^ (jj & 1));
                    mbar_wait(BAR(B_WEMPTY + 4 + j));
                    tma2d(sb + wstage(j), &M.m[tmW4], c0, c1, BAR(B_WFULL + 8 + j));
                }
            }
        } else {
            if ((sb & 0x3FFFF) != SMEM_BASE) __trap();
            mbar_wait_b(BAR(B_TILE)); mbar_wait_b(BAR(B_TILE + 1));
#pragma unroll 1
            for (int n = lane; n < 224; n += 32) {
                uint32_t v; int it = 0;
                do { v = ldr32(&G.u4[224 * fs + n]); if (++it > SPIN_MAX) __trap(); } while (any(v ^ ep));
                v = split2(__uint_as_float(v));
                sts128(sb + SM_U4 + 16 * n, make_uint4(prmt(v, v, 0x3232u), prmt(v, v, 0x1010u), 0u, 0u));
            }
            fence_async_smem();
            warp_arrive(BAR(B_U + 1));
            mbar_wait_b(BAR(B_DONE));
        }
    }
}

#undef G

typedef CUresult (*EncodeFn)(CUtensorMap*, CUtensorMapDataType, cuuint32_t, void*, const cuuint64_t*, const cuuint64_t*,
                             const cuuint32_t*, const cuuint32_t*, CUtensorMapInterleave, CUtensorMapSwizzle,
                             CUtensorMapL2promotion, CUtensorMapFloatOOBfill);

void encode(EncodeFn fn, CUtensorMap* m, const void* base, int rank, const cuuint64_t* dim, const cuuint64_t* stride,
            const cuuint32_t* box, CUtensorMapSwizzle sw) {
    const cuuint32_t es[5] = {1, 1, 1, 1, 1};
    fn(m, CU_TENSOR_MAP_DATA_TYPE_BFLOAT16, rank, const_cast<void*>(base), dim, stride, box, es, CU_TENSOR_MAP_INTERLEAVE_NONE,
       sw, CU_TENSOR_MAP_L2_PROMOTION_L2_128B, CU_TENSOR_MAP_FLOAT_OOB_FILL_NONE);
}

}

extern "C" void kernel_launch(void* const* d_in, const int* in_sizes, int n_in, void* d_out, int out_size) {
    (void)in_sizes; (void)n_in; (void)out_size;
    Params P;
    P.x = (const bf16*)d_in[0]; P.Are = (const bf16*)d_in[1]; P.Aim = (const bf16*)d_in[2]; P.Bre = (const bf16*)d_in[3];
    P.Bim = (const bf16*)d_in[4]; P.Cre = (const bf16*)d_in[5]; P.Cim = (const bf16*)d_in[6]; P.logdt = (const bf16*)d_in[7];
    P.dskip = (const bf16*)d_in[8]; P.w1 = (const bf16*)d_in[10]; P.w2 = (const bf16*)d_in[11]; P.w3 = (const bf16*)d_in[12];
    P.w4 = (const bf16*)d_in[13]; P.c = (const bf16*)d_in[14]; P.wmod = (const bf16*)d_in[15]; P.out = (bf16*)d_out;

    void* fnp = nullptr;
    cudaDriverEntryPointQueryResult qr;
    cudaGetDriverEntryPoint("cuTensorMapEncodeTiled", &fnp, cudaEnableDefault, &qr);
    EncodeFn fn = (EncodeFn)fnp;
    cudaFuncSetAttribute(fused_kernel, cudaFuncAttributeMaxDynamicSharedMemorySize, SM_TOTAL);
    void* pgs;
    cudaGetSymbolAddress(&pgs, g_scratch);
    Scratch* gs = P.gs = (Scratch*)pgs;
    const void *px2 = gs->x2t, *pg = gs->g, *px1 = gs->x1;
    Maps M;
    { const cuuint64_t d[2] = {2048, 512}, st[1] = {4096}; const cuuint32_t bx[2] = {64, 64}; encode(fn, &M.m[tmX2], px2, 2, d, st, bx, CU_TENSOR_MAP_SWIZZLE_128B); }
    { const cuuint64_t d[2] = {512, 2048}, st[1] = {1024}; const cuuint32_t bx[2] = {64, 64};
      encode(fn, &M.m[tmG], pg, 2, d, st, bx, CU_TENSOR_MAP_SWIZZLE_128B); encode(fn, &M.m[tmX1], px1, 2, d, st, bx, CU_TENSOR_MAP_SWIZZLE_128B); }
    { const cuuint64_t d[2] = {512, 512}, st[1] = {1024}; const cuuint32_t bx[2] = {64, 256}; encode(fn, &M.m[tmW1], P.w1, 2, d, st, bx, CU_TENSOR_MAP_SWIZZLE_128B); }
    { const cuuint64_t d[5] = {512, 2, 4, 4, 16}, st[4] = {1024, 8192, 2048, 32768}; const cuuint32_t bx[5] = {64, 2, 4, 4, 16};
      encode(fn, &M.m[tmW2], P.w2, 5, d, st, bx, CU_TENSOR_MAP_SWIZZLE_128B); }
    { const cuuint64_t d[5] = {32, 2, 64, 4, 56}, st[4] = {3584, 8 * 3584, 2 * 3584, 64}; const cuuint32_t bx[5] = {32, 2, 4, 4, 7};
      encode(fn, &M.m[tmW3], P.w3, 5, d, st, bx, CU_TENSOR_MAP_SWIZZLE_64B); }
    { const cuuint64_t d[2] = {512, 1792}, st[1] = {1024}; const cuuint32_t bx[2] = {64, 224}; encode(fn, &M.m[tmW4], P.w4, 2, d, st, bx, CU_TENSOR_MAP_SWIZZLE_128B); }
    { const cuuint64_t d[2] = {512, 2048}, st[1] = {1024}; const cuuint32_t bx[2] = {8, 256}; encode(fn, &M.m[tmXc], P.x, 2, d, st, bx, CU_TENSOR_MAP_SWIZZLE_NONE); }
    { const cuuint64_t d[2] = {3072, 512}, st[1] = {6144}; const cuuint32_t bx[2] = {64, 64}; encode(fn, &M.m[tmWm], P.wmod, 2, d, st, bx, CU_TENSOR_MAP_SWIZZLE_128B); }
    { const cuuint64_t d[2] = {1792, 512}, st[1] = {3584}; const cuuint32_t bx[2] = {16, 256}; encode(fn, &M.m[tmW3c], P.w3, 2, d, st, bx, CU_TENSOR_MAP_SWIZZLE_NONE); }

    cudaLaunchConfig_t cfg = {};
    cfg.gridDim = dim3(128); cfg.blockDim = dim3(384); cfg.dynamicSmemBytes = SM_TOTAL; cfg.stream = cudaStreamPerThread;
    cudaLaunchAttribute at[1];
    at[0].id = cudaLaunchAttributeClusterDimension; at[0].val.clusterDim.x = 2; at[0].val.clusterDim.y = 1; at[0].val.clusterDim.z = 1;
    cfg.attrs = at; cfg.numAttrs = 1;
    cudaLaunchKernelEx(&cfg, fused_kernel, P, M);
}
```

```cpp
#include <cuda_runtime.h>
#include <cuda_bf16.h>
#include <cuda.h>
#include <stdint.h>

namespace {

typedef __nv_bfloat16 bf16;

constexpr int SM_W1 = 0, SM_W2 = 65536, SM_Q = 131072, NSLOT = 11, SM_MISC = SM_Q + NSLOT * 8192;
constexpr int PT_PITCH = 272, PT_B = 24 * PT_PITCH + 1024;
constexpr int UW_B = 10880, SM_UW = SM_W2, XS_B = 10304, SM_XS = SM_UW + 4 * UW_B;
constexpr int WD_B = 3104, SM_WD = SM_Q, SM_SCV = SM_WD + 4 * WD_B;
constexpr int SM_ST = SM_Q + 2 * 8192, SM_WM = SM_Q + 4 * 8192, SM_XC = SM_Q + 7 * 8192, SM_DEP = SM_XC;
constexpr int SM_U4 = SM_W1 + 57344;
constexpr int SM_W3C = SM_W2 + 57344;
constexpr int SM_H = SM_Q + 4 * 8192;
constexpr int SM_BAR = SM_MISC;
constexpr int SM_CBV = SM_BAR + 1152;
constexpr int SM_ONE = SM_CBV + 2048;
constexpr int SM_U123 = SM_ONE + 128;
constexpr int SM_GB = SM_U123 + 2048;
constexpr int SM_RED = SM_GB + 256;
constexpr int SM_ARED = SM_RED + 1536;
constexpr int SM_OWN = SM_ARED + 512;
constexpr int SM_CONST = SM_OWN + 64;
constexpr int SM_TS = SM_CONST + 64;
constexpr int SM_TOTAL = SM_TS + 384;
static_assert(SM_XS + 2 * XS_B <= SM_Q, "conv buffers");
static_assert(SM_TOTAL <= 232448, "smem");
constexpr int T0o = 8, T4o = 288, T2o = 432, TM2o = 512, T1o = 592, T3o = 640, T5o = 688, TM1o = 736;
constexpr int B_WM = 0  , B_XC = 3  , B_ST = 5, B_EARLY = 6,
              B_FULL = 8  ,
              B_WFULL = 56  , B_HFULL = 72  , B_W1FULL = 74, B_W3C = 76  ,
              B_MOD = 78  , B_U4 = 80, B_SEEN = 81  , B_WEMPTY = 83  , B_DONE = 95,
              B_NEAR = 96  , B_EMPTY = 112  , B_TILE = 128  , B_CONV = 132  ,
              B_UB = 134  , B_W2FULL = 140  , B_HFREE = 136  , B_W1RDY = 138;

constexpr float LN_EPS = 1e-5f;
constexpr int SPIN_MAX = 1 << 20;

struct Scratch {
    bf16 x2t[512 * 2048], g[2048 * 512], x1[2048 * 512];
    uint4 part[16 * 8 * 3 * 2 * 512];
    uint4 stats1[2048];
    float2 stats2[2048 * 8];
    uint32_t stats0[2048];
    uint32_t modq[8 * 3072];
    uint4 modp[128 * 2];
    uint32_t u4[1792];
    uint32_t cnt[2 * 8 * 32], flag[2 * 32 * 8 * 32], epoch[128];
};
__device__ __align__(1024) Scratch g_scratch;

struct Params {
    const bf16 *x, *Are, *Aim, *Bre, *Bim, *Cre, *Cim, *logdt, *dskip, *w1, *w2, *w3, *w4, *c, *wmod;
    bf16* out;
    Scratch* gs;
};

enum { tmX2, tmG, tmX1, tmWm, tmXc, tmW3c, tmW1, tmW2, tmW3, tmW4, tmCount };
struct Maps { CUtensorMap m[tmCount]; };

__device__ __forceinline__ void mbar_init(uint32_t b, int c) { asm volatile("mbarrier.init.shared::cta.b64 [%0], %1;" ::"r"(b), "r"(c) : "memory"); }
__device__ __forceinline__ void mbar_expect(uint32_t b, int bytes) { asm volatile("mbarrier.arrive.expect_tx.shared::cta.b64 _, [%0], %1;" ::"r"(b), "r"(bytes) : "memory"); }
__device__ __forceinline__ void mbar_arrive(uint32_t b) { asm volatile("mbarrier.arrive.shared::cta.b64 _, [%0];" ::"r"(b) : "memory"); }
__device__ __forceinline__ void mbar_arrive_remote(uint32_t b) { asm volatile("mbarrier.arrive.relaxed.cluster.shared::cluster.b64 _, [%0];" ::"r"(b) : "memory"); }
__device__ __forceinline__ bool mbar_test(uint32_t b) {
    uint32_t ok;
    asm volatile("{.reg .pred p; mbarrier.test_wait.parity.shared::cta.b64 p, [%1], 0; selp.u32 %0, 1, 0, p;}" : "=r"(ok) : "r"(b) : "memory");
    return ok;
}
__device__ __forceinline__ void mbar_wait(uint32_t b) {
    asm volatile("{.reg .pred p; W: mbarrier.try_wait.parity.shared::cta.b64 p, [%0], 0; @!p bra W;}" ::"r"(b) : "memory");
}
__device__ __forceinline__ void mbar_wait_cluster(uint32_t b) {
    asm volatile("{.reg .pred p; W: mbarrier.try_wait.parity.acquire.cluster.shared::cta.b64 p, [%0], 0; @!p bra W;}" ::"r"(b) : "memory");
}
__device__ __forceinline__ void mbar_wait_b(uint32_t b) {
    uint32_t ok; int it = 0;
    do {
        asm volatile("{.reg .pred p; mbarrier.try_wait.parity.shared::cta.b64 p, [%1], 0; selp.u32 %0, 1, 0, p;}" : "=r"(ok) : "r"(b) : "memory");
        if (++it > SPIN_MAX) __trap();
    } while (!ok);
}
__device__ __forceinline__ bool any(uint32_t bad) { return __any_sync(0xffffffffu, bad & 1); }
__device__ __forceinline__ void warp_arrive(uint32_t b) { __syncwarp(); if ((threadIdx.x & 31) == 0) mbar_arrive(b); }
__device__ __forceinline__ void bar_sync(int id, int n) { asm volatile("bar.sync %0, %1;" ::"r"(id), "r"(n) : "memory"); }
__device__ __forceinline__ void fence_async_smem() { asm volatile("fence.proxy.async.shared::cta;" ::: "memory"); }
__device__ __forceinline__ void fence_acquire() { asm volatile("fence.acquire.gpu;" ::: "memory"); }
__device__ __forceinline__ void fence_async_global() { asm volatile("fence.proxy.async.global;" ::: "memory"); }
__device__ __forceinline__ uint32_t mapa(uint32_t a, uint32_t r) { uint32_t d; asm("mapa.shared::cluster.u32 %0, %1, %2;" : "=r"(d) : "r"(a), "r"(r)); return d; }

__device__ __forceinline__ void tma2d(uint32_t dst, const CUtensorMap* m, int c0, int c1, uint32_t bar) {
    asm volatile("cp.async.bulk.tensor.2d.shared::cluster.global.mbarrier::complete_tx::bytes [%0], [%1, {%3, %4}], [%2];"
                 ::"r"(dst), "l"(m), "r"(bar), "r"(c0), "r"(c1) : "memory");
}
__device__ __forceinline__ void tma2d_pair(uint32_t dst, const CUtensorMap* m, int c0, int c1, uint32_t bar) {
    asm volatile("cp.async.bulk.tensor.2d.shared::cluster.global.mbarrier::complete_tx::bytes.multicast::cluster [%0], [%1, {%3, %4}], [%2], %5;"
                 ::"r"(dst), "l"(m), "r"(bar), "r"(c0), "r"(c1), "h"((unsigned short)3) : "memory");
}
__device__ __forceinline__ void tma5d(uint32_t dst, const CUtensorMap* m, int c0, int c1, int c2, int c3, int c4, uint32_t bar) {
    asm volatile("cp.async.bulk.tensor.5d.shared::cluster.global.mbarrier::complete_tx::bytes [%0], [%1, {%3, %4, %5, %6, %7}], [%2];"
                 ::"r"(dst), "l"(m), "r"(bar), "r"(c0), "r"(c1), "r"(c2), "r"(c3), "r"(c4) : "memory");
}
__device__ __forceinline__ void l2_prefetch(const void* p, int bytes) { asm volatile("cp.async.bulk.prefetch.L2.global [%0], %1;" ::"l"(p), "r"(bytes) : "memory"); }

__device__ __forceinline__ uint32_t lds32(uint32_t a) { uint32_t v; asm volatile("ld.shared.b32 %0, [%1];" : "=r"(v) : "r"(a)); return v; }
__device__ __forceinline__ uint2 lds64(uint32_t a) { uint2 v; asm volatile("ld.shared.v2.b32 {%0,%1}, [%2];" : "=r"(v.x), "=r"(v.y) : "r"(a)); return v; }
__device__ __forceinline__ uint4 lds128(uint32_t a) { uint4 v; asm volatile("ld.shared.v4.b32 {%0,%1,%2,%3}, [%4];" : "=r"(v.x), "=r"(v.y), "=r"(v.z), "=r"(v.w) : "r"(a)); return v; }
__device__ __forceinline__ float2 ldsf2(uint32_t a) { uint2 v = lds64(a); return make_float2(__uint_as_float(v.x), __uint_as_float(v.y)); }
__device__ __forceinline__ void sts16(uint32_t a, uint32_t v) { asm volatile("st.shared.b16 [%0], %1;" ::"r"(a), "h"((unsigned short)v) : "memory"); }
__device__ __forceinline__ void sts32(uint32_t a, uint32_t v) { asm volatile("st.shared.b32 [%0], %1;" ::"r"(a), "r"(v) : "memory"); }
__device__ __forceinline__ void stsf(uint32_t a, float v) { sts32(a, __float_as_uint(v)); }
__device__ __forceinline__ void sts64(uint32_t a, uint32_t x, uint32_t y) { asm volatile("st.shared.v2.b32 [%0], {%1,%2};" ::"r"(a), "r"(x), "r"(y) : "memory"); }
__device__ __forceinline__ void sts128(uint32_t a, uint4 v) { asm volatile("st.shared.v4.b32 [%0], {%1,%2,%3,%4};" ::"r"(a), "r"(v.x), "r"(v.y), "r"(v.z), "r"(v.w) : "memory"); }
__device__ __forceinline__ void ldsm4(uint32_t* r, uint32_t a) { asm volatile("ldmatrix.sync.aligned.m8n8.x4.shared.b16 {%0,%1,%2,%3}, [%4];" : "=r"(r[0]), "=r"(r[1]), "=r"(r[2]), "=r"(r[3]) : "r"(a)); }
__device__ __forceinline__ void ldsm2t(uint32_t* r, uint32_t a) { asm volatile("ldmatrix.sync.aligned.m8n8.x2.trans.shared.b16 {%0,%1}, [%2];" : "=r"(r[0]), "=r"(r[1]) : "r"(a)); }
__device__ __forceinline__ void ldsm4t(uint32_t* r, uint32_t a) { asm volatile("ldmatrix.sync.aligned.m8n8.x4.trans.shared.b16 {%0,%1,%2,%3}, [%4];" : "=r"(r[0]), "=r"(r[1]), "=r"(r[2]), "=r"(r[3]) : "r"(a)); }
__device__ __forceinline__ void stsm4t(uint32_t a, uint32_t r0, uint32_t r1, uint32_t r2, uint32_t r3) { asm volatile("stmatrix.sync.aligned.m8n8.x4.trans.shared.b16 [%0], {%1,%2,%3,%4};" ::"r"(a), "r"(r0), "r"(r1), "r"(r2), "r"(r3) : "memory"); }
__device__ __forceinline__ void stsm4(uint32_t a, uint32_t r0, uint32_t r1, uint32_t r2, uint32_t r3) { asm volatile("stmatrix.sync.aligned.m8n8.x4.shared.b16 [%0], {%1,%2,%3,%4};" ::"r"(a), "r"(r0), "r"(r1), "r"(r2), "r"(r3) : "memory"); }

__device__ __forceinline__ uint32_t ldg16(const void* p) { uint32_t v; asm volatile("ld.global.nc.u16 %0, [%1];" : "=r"(v) : "l"(p)); return v; }
__device__ __forceinline__ uint32_t ldg32(const void* p) { uint32_t v; asm volatile("ld.global.nc.b32 %0, [%1];" : "=r"(v) : "l"(p)); return v; }
__device__ __forceinline__ uint4 ldg128(const void* p) { uint4 v; asm volatile("ld.global.nc.L1::no_allocate.v4.b32 {%0,%1,%2,%3}, [%4];" : "=r"(v.x), "=r"(v.y), "=r"(v.z), "=r"(v.w) : "l"(p)); return v; }
__device__ __forceinline__ uint32_t ldr32(const void* p) { uint32_t v; asm volatile("ld.relaxed.gpu.global.b32 %0, [%1];" : "=r"(v) : "l"(p) : "memory"); return v; }
__device__ __forceinline__ uint2 ldr64(const void* p) { uint2 v; asm volatile("{.reg .b64 t; ld.relaxed.gpu.global.b64 t, [%2]; mov.b64 {%0,%1}, t;}" : "=r"(v.x), "=r"(v.y) : "l"(p) : "memory"); return v; }
__device__ __forceinline__ uint4 ldr128(const void* p) { uint4 v; asm volatile("{.reg .b128 t; ld.relaxed.gpu.global.b128 t, [%4]; mov.b128 {%0,%1,%2,%3}, t;}" : "=r"(v.x), "=r"(v.y), "=r"(v.z), "=r"(v.w) : "l"(p) : "memory"); return v; }
__device__ __forceinline__ void str32(void* p, uint32_t v) { asm volatile("st.relaxed.gpu.global.b32 [%0], %1;" ::"l"(p), "r"(v) : "memory"); }
__device__ __forceinline__ void str64(void* p, uint32_t x, uint32_t y) { asm volatile("{.reg .b64 t; mov.b64 t, {%1,%2}; st.relaxed.gpu.global.b64 [%0], t;}" ::"l"(p), "r"(x), "r"(y) : "memory"); }
__device__ __forceinline__ void str128(void* p, uint4 v) { asm volatile("{.reg .b128 t; mov.b128 t, {%1,%2,%3,%4}; st.relaxed.gpu.global.b128 [%0], t;}" ::"l"(p), "r"(v.x), "r"(v.y), "r"(v.z), "r"(v.w) : "memory"); }
__device__ __forceinline__ void stg32(void* p, uint32_t v) { asm volatile("st.global.b32 [%0], %1;" ::"l"(p), "r"(v) : "memory"); }
__device__ __forceinline__ void stg128(void* p, uint32_t x, uint32_t y, uint32_t z, uint32_t w) { asm volatile("st.global.v4.b32 [%0], {%1,%2,%3,%4};" ::"l"(p), "r"(x), "r"(y), "r"(z), "r"(w) : "memory"); }
__device__ __forceinline__ uint32_t fbits(float f) { return __float_as_uint(f); }
__device__ __forceinline__ uint32_t tagw(uint32_t w, uint32_t ep) { uint32_t r; asm("lop3.b32 %0, %1, %2, 1, 0xD8;" : "=r"(r) : "r"(w), "r"(ep)); return r; }
__device__ __forceinline__ uint32_t tagf(float f, uint32_t ep) { return tagw(fbits(f), ep); }
__device__ __forceinline__ uint32_t stale(uint32_t bad, uint32_t w, uint32_t ep) { uint32_t r; asm("lop3.b32 %0, %1, %2, %3, 0xF6;" : "=r"(r) : "r"(bad), "r"(w), "r"(ep)); return r; }

__device__ __forceinline__ uint32_t pack2(float lo, float hi) { uint32_t r; asm("cvt.rn.bf16x2.f32 %0, %1, %2;" : "=r"(r) : "f"(hi), "f"(lo)); return r; }
__device__ __forceinline__ float blo(uint32_t v) { return __uint_as_float(v << 16); }
__device__ __forceinline__ float bhi(uint32_t v) { return __uint_as_float(v & 0xFFFF0000u); }
__device__ __forceinline__ float bround(float v) { return blo(pack2(v, 0.f)); }
__device__ __forceinline__ uint32_t hadd2(uint32_t a, uint32_t b) { uint32_t r; asm("add.rn.bf16x2 %0, %1, %2;" : "=r"(r) : "r"(a), "r"(b)); return r; }
__device__ __forceinline__ uint32_t hmul2(uint32_t a, uint32_t b) { uint32_t r; asm("mul.rn.bf16x2 %0, %1, %2;" : "=r"(r) : "r"(a), "r"(b)); return r; }
__device__ __forceinline__ uint32_t hfma2(uint32_t a, uint32_t b, uint32_t c) { uint32_t r; asm("fma.rn.bf16x2 %0, %1, %2, %3;" : "=r"(r) : "r"(a), "r"(b), "r"(c)); return r; }
__device__ __forceinline__ uint32_t hnorm2(uint32_t x, uint32_t s) {
    uint32_t r;
    asm("{.reg .b16 l, h; .reg .b32 a, c; mov.b32 {l, h}, %2; mov.b32 a, {l, l}; mov.b32 c, {h, h}; add.rn.bf16x2 a, %1, a; mul.rn.bf16x2 %0, a, c;}" : "=r"(r) : "r"(x), "r"(s));
    return r;
}
__device__ __forceinline__ uint32_t prmt(uint32_t a, uint32_t b, uint32_t s) { uint32_t r; asm("prmt.b32 %0, %1, %2, %3;" : "=r"(r) : "r"(a), "r"(b), "r"(s)); return r; }
__device__ __forceinline__ float rcp(float v) { float r; asm("rcp.approx.ftz.f32 %0, %1;" : "=f"(r) : "f"(v)); return r; }
__device__ __forceinline__ float rsq(float v) { float r; asm("rsqrt.approx.ftz.f32 %0, %1;" : "=f"(r) : "f"(v)); return r; }
__device__ __forceinline__ float shx(float v, int m) { return __shfl_xor_sync(0xffffffffu, v, m); }
__device__ __forceinline__ float gelu_t(float v, float k0, float k1) {
    float t;
    asm("tanh.approx.f32 %0, %1;" : "=f"(t) : "f"(v * fmaf(v * k1, v, k0)));
    return t;
}
constexpr float GK0 = 0.7978845608028654f, GK1 = 0.0356774081363001f;
__device__ __forceinline__ uint32_t split2(float c) { const float h = bround(c); return pack2(c - h, h); }
struct cf { float x, y; };
__device__ __forceinline__ cf cmul(cf a, cf b) { cf r; r.x = fmaf(a.x, b.x, -a.y * b.y); r.y = fmaf(a.x, b.y, a.y * b.x); return r; }
__device__ __forceinline__ cf cexp2(float e, float th) {
    float m; asm("ex2.approx.ftz.f32 %0, %1;" : "=f"(m) : "f"(e));
    cf r; r.x = m * __cosf(th); r.y = m * __sinf(th); return r;
}

__device__ __forceinline__ void mma(float* d, uint32_t a0, uint32_t a1, uint32_t a2, uint32_t a3, uint32_t b0, uint32_t b1) {
    asm volatile("mma.sync.aligned.m16n8k16.row.col.f32.bf16.bf16.f32 {%0,%1,%2,%3},{%4,%5,%6,%7},{%8,%9},{%0,%1,%2,%3};"
                 : "+f"(d[0]), "+f"(d[1]), "+f"(d[2]), "+f"(d[3]) : "r"(a0), "r"(a1), "r"(a2), "r"(a3), "r"(b0), "r"(b1));
}
__device__ __forceinline__ void mmap(float* d, const uint32_t* a, const uint32_t* b) { mma(d, a[0], a[1], a[2], a[3], b[0], b[1]); }
__device__ __forceinline__ void mmar(float* d, const float* c, const uint32_t* a, const uint32_t* b) {
    asm volatile("mma.sync.aligned.m16n8k16.row.col.f32.bf16.bf16.f32 {%0,%1,%2,%3},{%4,%5,%6,%7},{%8,%9},{%10,%11,%12,%13};"
                 : "=f"(d[0]), "=f"(d[1]), "=f"(d[2]), "=f"(d[3])
                 : "r"(a[0]), "r"(a[1]), "r"(a[2]), "r"(a[3]), "r"(b[0]), "r"(b[1]), "f"(c[0]), "f"(c[1]), "f"(c[2]), "f"(c[3]));
}
__device__ __forceinline__ uint32_t cpy(uint32_t a, uint32_t z, int k) { return a + z * (uint32_t)k; }

#define WG_FENCE() asm volatile("wgmma.fence.sync.aligned;" ::: "memory")
#define WG_COMMIT() asm volatile("wgmma.commit_group.sync.aligned;" ::: "memory")
#define WG_WAIT(n) asm volatile("wgmma.wait_group.sync.aligned " #n ";" ::: "memory")
template <int N> __device__ __forceinline__ void pin(float* d) {
#pragma unroll
    for (int i = 0; i < N; i++) asm volatile("" : "+f"(d[i])::"memory");
}
template <int N> __device__ __forceinline__ void pinu(uint32_t* d) {
#pragma unroll
    for (int i = 0; i < N; i++) asm volatile("" : "+r"(d[i])::"memory");
}
constexpr uint32_t SMEM_BASE = 1024;
__device__ __forceinline__ uint32_t dlo(uint32_t off, uint32_t lbo) { return ((SMEM_BASE + off) >> 4) + ((lbo >> 4) << 16); }
template <int TA> __device__ __forceinline__ void wgmma_ss64(float* d, uint32_t da, uint32_t db, int sd) {
    asm volatile("{.reg .pred p; .reg .b64 a, b; setp.ne.b32 p, %34, 0; mov.b64 a, {%32, 0x40000040}; mov.b64 b, {%33, 0x40000040};\n"
                 "wgmma.mma_async.sync.aligned.m64n64k16.f32.bf16.bf16 {%0, %1, %2, %3, %4, %5, %6, %7, %8, %9, %10, %11, %12, %13, %14, %15, %16, %17, %18, %19, %20, %21, %22, %23, %24, %25, %26, %27, %28, %29, %30, %31}, a, b, p, 1, 1, %35, 1;}"
                 : "+f"(d[0]), "+f"(d[1]), "+f"(d[2]), "+f"(d[3]), "+f"(d[4]), "+f"(d[5]), "+f"(d[6]), "+f"(d[7]),
                   "+f"(d[8]), "+f"(d[9]), "+f"(d[10]), "+f"(d[11]), "+f"(d[12]), "+f"(d[13]), "+f"(d[14]), "+f"(d[15]),
                   "+f"(d[16]), "+f"(d[17]), "+f"(d[18]), "+f"(d[19]), "+f"(d[20]), "+f"(d[21]), "+f"(d[22]), "+f"(d[23]),
                   "+f"(d[24]), "+f"(d[25]), "+f"(d[26]), "+f"(d[27]), "+f"(d[28]), "+f"(d[29]), "+f"(d[30]), "+f"(d[31])
                 : "r"(da), "r"(db), "r"(sd), "n"(TA));
}
__device__ __forceinline__ void wgmma_ss224(float* d, uint32_t da, uint32_t db, int sd) {
    asm volatile("{.reg .pred p; .reg .b64 a, b; setp.ne.b32 p, %114, 0; mov.b64 a, {%112, 0x40000040}; mov.b64 b, {%113, 0x80000020};\n"
                 "wgmma.mma_async.sync.aligned.m64n224k16.f32.bf16.bf16 {%0, %1, %2, %3, %4, %5, %6, %7, %8, %9, %10, %11, %12, %13, %14, %15, %16, %17, %18, %19, %20, %21, %22, %23, %24, %25, %26, %27, %28, %29, %30, %31, %32, %33, %34, %35, %36, %37, %38, %39, %40, %41, %42, %43, %44, %45, %46, %47, %48, %49, %50, %51, %52, %53, %54, %55, %56, %57, %58, %59, %60, %61, %62, %63, %64, %65, %66, %67, %68, %69, %70, %71, %72, %73, %74, %75, %76, %77, %78, %79, %80, %81, %82, %83, %84, %85, %86, %87, %88, %89, %90, %91, %92, %93, %94, %95, %96, %97, %98, %99, %100, %101, %102, %103, %104, %105, %106, %107, %108, %109, %110, %111}, a, b, p, 1, 1, %115, 1;}"
                 : "+f"(d[0]), "+f"(d[1]), "+f"(d[2]), "+f"(d[3]), "+f"(d[4]), "+f"(d[5]), "+f"(d[6]), "+f"(d[7]),
                   "+f"(d[8]), "+f"(d[9]), "+f"(d[10]), "+f"(d[11]), "+f"(d[12]), "+f"(d[13]), "+f"(d[14]), "+f"(d[15]),
                   "+f"(d[16]), "+f"(d[17]), "+f"(d[18]), "+f"(d[19]), "+f"(d[20]), "+f"(d[21]), "+f"(d[22]), "+f"(d[23]),
                   "+f"(d[24]), "+f"(d[25]), "+f"(d[26]), "+f"(d[27]), "+f"(d[28]), "+f"(d[29]), "+f"(d[30]), "+f"(d[31]),
                   "+f"(d[32]), "+f"(d[33]), "+f"(d[34]), "+f"(d[35]), "+f"(d[36]), "+f"(d[37]), "+f"(d[38]), "+f"(d[39]),
                   "+f"(d[40]), "+f"(d[41]), "+f"(d[42]), "+f"(d[43]), "+f"(d[44]), "+f"(d[45]), "+f"(d[46]), "+f"(d[47]),
                   "+f"(d[48]), "+f"(d[49]), "+f"(d[50]), "+f"(d[51]), "+f"(d[52]), "+f"(d[53]), "+f"(d[54]), "+f"(d[55]),
                   "+f"(d[56]), "+f"(d[57]), "+f"(d[58]), "+f"(d[59]), "+f"(d[60]), "+f"(d[61]), "+f"(d[62]), "+f"(d[63]),
                   "+f"(d[64]), "+f"(d[65]), "+f"(d[66]), "+f"(d[67]), "+f"(d[68]), "+f"(d[69]), "+f"(d[70]), "+f"(d[71]),
                   "+f"(d[72]), "+f"(d[73]), "+f"(d[74]), "+f"(d[75]), "+f"(d[76]), "+f"(d[77]), "+f"(d[78]), "+f"(d[79]),
                   "+f"(d[80]), "+f"(d[81]), "+f"(d[82]), "+f"(d[83]), "+f"(d[84]), "+f"(d[85]), "+f"(d[86]), "+f"(d[87]),
                   "+f"(d[88]), "+f"(d[89]), "+f"(d[90]), "+f"(d[91]), "+f"(d[92]), "+f"(d[93]), "+f"(d[94]), "+f"(d[95]),
                   "+f"(d[96]), "+f"(d[97]), "+f"(d[98]), "+f"(d[99]), "+f"(d[100]), "+f"(d[101]), "+f"(d[102]), "+f"(d[103]),
                   "+f"(d[104]), "+f"(d[105]), "+f"(d[106]), "+f"(d[107]), "+f"(d[108]), "+f"(d[109]), "+f"(d[110]), "+f"(d[111])
                 : "r"(da), "r"(db), "r"(sd), "n"(0));
}
template <int TB> __device__ __forceinline__ void wgmma_rs64(float* d, uint32_t a0, uint32_t a1, uint32_t a2, uint32_t a3, uint32_t db, int sd) {
    asm volatile("{.reg .pred p; .reg .b64 b; setp.ne.b32 p, %37, 0; mov.b64 b, {%36, %39};\n"
                 "wgmma.mma_async.sync.aligned.m64n64k16.f32.bf16.bf16 {%0, %1, %2, %3, %4, %5, %6, %7, %8, %9, %10, %11, %12, %13, %14, %15, %16, %17, %18, %19, %20, %21, %22, %23, %24, %25, %26, %27, %28, %29, %30, %31}, {%32, %33, %34, %35}, b, p, 1, 1, %38;}"
                 : "+f"(d[0]), "+f"(d[1]), "+f"(d[2]), "+f"(d[3]), "+f"(d[4]), "+f"(d[5]), "+f"(d[6]), "+f"(d[7]),
                   "+f"(d[8]), "+f"(d[9]), "+f"(d[10]), "+f"(d[11]), "+f"(d[12]), "+f"(d[13]), "+f"(d[14]), "+f"(d[15]),
                   "+f"(d[16]), "+f"(d[17]), "+f"(d[18]), "+f"(d[19]), "+f"(d[20]), "+f"(d[21]), "+f"(d[22]), "+f"(d[23]),
                   "+f"(d[24]), "+f"(d[25]), "+f"(d[26]), "+f"(d[27]), "+f"(d[28]), "+f"(d[29]), "+f"(d[30]), "+f"(d[31])
                 : "r"(a0), "r"(a1), "r"(a2), "r"(a3), "r"(db), "r"(sd), "n"(TB), "n"(TB ? 0x40000040 : 8));
}
__device__ __forceinline__ void wgmma_rs224(float* d, uint32_t a0, uint32_t a1, uint32_t a2, uint32_t a3, uint32_t db, int sd) {
    asm volatile("{.reg .pred p; .reg .b64 b; setp.ne.b32 p, %117, 0; mov.b64 b, {%116, %119};\n"
                 "wgmma.mma_async.sync.aligned.m64n224k16.f32.bf16.bf16 {%0, %1, %2, %3, %4, %5, %6, %7, %8, %9, %10, %11, %12, %13, %14, %15, %16, %17, %18, %19, %20, %21, %22, %23, %24, %25, %26, %27, %28, %29, %30, %31, %32, %33, %34, %35, %36, %37, %38, %39, %40, %41, %42, %43, %44, %45, %46, %47, %48, %49, %50, %51, %52, %53, %54, %55, %56, %57, %58, %59, %60, %61, %62, %63, %64, %65, %66, %67, %68, %69, %70, %71, %72, %73, %74, %75, %76, %77, %78, %79, %80, %81, %82, %83, %84, %85, %86, %87, %88, %89, %90, %91, %92, %93, %94, %95, %96, %97, %98, %99, %100, %101, %102, %103, %104, %105, %106, %107, %108, %109, %110, %111}, {%112, %113, %114, %115}, b, p, 1, 1, %118;}"
                 : "+f"(d[0]), "+f"(d[1]), "+f"(d[2]), "+f"(d[3]), "+f"(d[4]), "+f"(d[5]), "+f"(d[6]), "+f"(d[7]),
                   "+f"(d[8]), "+f"(d[9]), "+f"(d[10]), "+f"(d[11]), "+f"(d[12]), "+f"(d[13]), "+f"(d[14]), "+f"(d[15]),
                   "+f"(d[16]), "+f"(d[17]), "+f"(d[18]), "+f"(d[19]), "+f"(d[20]), "+f"(d[21]), "+f"(d[22]), "+f"(d[23]),
                   "+f"(d[24]), "+f"(d[25]), "+f"(d[26]), "+f"(d[27]), "+f"(d[28]), "+f"(d[29]), "+f"(d[30]), "+f"(d[31]),
                   "+f"(d[32]), "+f"(d[33]), "+f"(d[34]), "+f"(d[35]), "+f"(d[36]), "+f"(d[37]), "+f"(d[38]), "+f"(d[39]),
                   "+f"(d[40]), "+f"(d[41]), "+f"(d[42]), "+f"(d[43]), "+f"(d[44]), "+f"(d[45]), "+f"(d[46]), "+f"(d[47]),
                   "+f"(d[48]), "+f"(d[49]), "+f"(d[50]), "+f"(d[51]), "+f"(d[52]), "+f"(d[53]), "+f"(d[54]), "+f"(d[55]),
                   "+f"(d[56]), "+f"(d[57]), "+f"(d[58]), "+f"(d[59]), "+f"(d[60]), "+f"(d[61]), "+f"(d[62]), "+f"(d[63]),
                   "+f"(d[64]), "+f"(d[65]), "+f"(d[66]), "+f"(d[67]), "+f"(d[68]), "+f"(d[69]), "+f"(d[70]), "+f"(d[71]),
                   "+f"(d[72]), "+f"(d[73]), "+f"(d[74]), "+f"(d[75]), "+f"(d[76]), "+f"(d[77]), "+f"(d[78]), "+f"(d[79]),
                   "+f"(d[80]), "+f"(d[81]), "+f"(d[82]), "+f"(d[83]), "+f"(d[84]), "+f"(d[85]), "+f"(d[86]), "+f"(d[87]),
                   "+f"(d[88]), "+f"(d[89]), "+f"(d[90]), "+f"(d[91]), "+f"(d[92]), "+f"(d[93]), "+f"(d[94]), "+f"(d[95]),
                   "+f"(d[96]), "+f"(d[97]), "+f"(d[98]), "+f"(d[99]), "+f"(d[100]), "+f"(d[101]), "+f"(d[102]), "+f"(d[103]),
                   "+f"(d[104]), "+f"(d[105]), "+f"(d[106]), "+f"(d[107]), "+f"(d[108]), "+f"(d[109]), "+f"(d[110]), "+f"(d[111])
                 : "r"(a0), "r"(a1), "r"(a2), "r"(a3), "r"(db), "r"(sd), "n"(0), "n"(0 ? 0x40000040 : 8));
}


__device__ __forceinline__ uint32_t vecpos(int kw) { return (kw >> 4) * 64 + (kw & 3) * 16 + ((kw >> 2) & 1) * 8 + ((kw >> 3) & 1) * 4; }

__device__ __forceinline__ uint32_t wstage(int q) { return (q & 1) * 28672 + (q & 2) * 32768; }

__global__ void __launch_bounds__(384, 1)
fused_kernel(const Params P, const __grid_constant__ Maps M)
{
    extern __shared__ __align__(1024) uint8_t smem_raw[];
    const uint32_t sb = __shfl_sync(0xffffffffu, (uint32_t)__cvta_generic_to_shared(smem_raw), 0);
    const int tid = threadIdx.x, lane = tid & 31, warp = __shfl_sync(0xffffffffu, tid >> 5, 0), g = lane >> 2, q = lane & 3;
    const int cl = blockIdx.x >> 1, pr = blockIdx.x & 1;
    int gi, pa;
    if (cl < 4) { gi = 15; pa = cl; } else if (cl < 36) { gi = (cl - 4) & 7; pa = (cl - 4) >> 3; } else { gi = 8 + (cl - 36) % 7; pa = (cl - 36) / 7; }
    const int fs = 2 * pa + pr;
    const int cs = 4 * pr + pa;
    const int b = 8 * gi + fs;
    const uint32_t bar0 = sb + SM_BAR;
#define BAR(i) (bar0 + 8 * (i))
#define G (*P.gs)

    if (warp < 8) {
        const int s = warp >> 2, w4 = warp & 3, wt = tid & 127;
        asm volatile("barrier.cluster.arrive.relaxed.aligned;" ::: "memory");
        const size_t po = (size_t)b * 512 + 2 * tid;
        const uint32_t ldt = ldg16(P.logdt + 4 * b + (warp >> 1));
        const uint32_t pAre = ldg32(P.Are + po), pAim = ldg32(P.Aim + po), pBre = ldg32(P.Bre + po), pBim = ldg32(P.Bim + po),
                       pCre = ldg32(P.Cre + po), pCim = ldg32(P.Cim + po);
        const uint32_t dsk = ldg16(P.dskip + 4 * b + (warp >> 1));
        uint32_t ep = ldr32(&G.epoch[b]);
        asm volatile("setmaxnreg.inc.sync.aligned.u32 224;");
#pragma unroll
        for (int i = 0; i < 3; i++) sts128(sb + SM_WD + (tid + 256 * i) * 16, make_uint4(0, 0, 0, 0));
        if (tid < 168) sts128(tid < 8 ? sb + SM_WD + (768 + tid) * 16 : sb + SM_UW + ((tid - 8) / 40) * UW_B + ((tid - 8) % 40) * 16, make_uint4(0, 0, 0, 0));
        {
            const int mh = warp & 1;
            uint32_t sa_[3][2];
            {
                const uint32_t wd = sb + SM_WD + (warp >> 1) * WD_B + (16 * mh + g) * 4, sel = 0x4410u + 0x22u * (q & 1);
#define CBW(a, c) ((uint32_t)(4 * (a)) | ((uint32_t)(4 * (c)) << 16))
#define CBS(a, c, d, e) (wd + prmt(q & 2 ? CBW(d, e) : CBW(a, c), 0u, sel))
                sa_[0][0] = CBS(T0o, T2o, T4o, TM2o + 1); sa_[0][1] = CBS(T1o, T3o, T5o, TM1o + 1);
                sa_[1][0] = CBS(T0o + 32, T4o + 32, T0o + 64, T0o + 96); sa_[1][1] = CBS(T2o + 32, TM2o + 33, T4o + 64, T4o + 96);
                sa_[2][0] = wd + 4 * (T0o + 128) + 256 * q; sa_[2][1] = sa_[2][0] + 128;
#undef CBW
#undef CBS
                pinu<6>(&sa_[0][0]);
            }
            const uint32_t pt = sb + SM_W1 + warp * PT_B;
            {
                const float dt = bround(expf(blo(ldt)));
                cf z[2], w[2], r0[2], r2[2], r4[2], t[2];
#pragma unroll
                for (int m = 0; m < 2; m++) {
                    const float a = dt * (m ? bhi(pAre) : blo(pAre)) * 1.4426950408889634f, th = dt * (m ? bhi(pAim) : blo(pAim));
                    const cf z64 = cexp2(64.f * a, 64.f * th);
                    sts128(pt + 24 * PT_PITCH + lane * 32 + m * 16, make_uint4(__float_as_uint(8.f * a), __float_as_uint(8.f * th), __float_as_uint(z64.x), __float_as_uint(z64.y)));
                    z[m] = cexp2(a, -th); w[m] = cexp2(256.f * a, -256.f * th);
                    cf C, B;
                    C.x = m ? bhi(pCre) : blo(pCre); C.y = -(m ? bhi(pCim) : blo(pCim));
                    B.x = dt * (m ? bhi(pBre) : blo(pBre)); B.y = -dt * (m ? bhi(pBim) : blo(pBim));
                    r0[m] = cmul(C, B);
                }
                const uint32_t pp = pt + lane * 8;
#define PST(j, v) sts64(pp + (j) * PT_PITCH, pack2(v[0].x, v[0].y), pack2(v[1].x, v[1].y))
#define CM(d, a, c) d[0] = cmul(a[0], c[0]); d[1] = cmul(a[1], c[1])
                PST(0, r0); CM(t, r0, z); PST(1, t); CM(r2, t, z); PST(2, r2); CM(t, r2, z); PST(3, t); CM(r4, t, z); PST(4, r4);
                CM(r2, r2, w); PST(9, r2); CM(t, r4, z); PST(5, t); CM(r2, t, z); PST(6, r2); CM(t, r2, z); PST(7, t); CM(r2, r2, w); PST(11, r2);
                CM(r0, r0, w); PST(8, r0); CM(r4, r4, w); PST(10, r4); CM(r0, r0, w); PST(12, r0); CM(r4, r4, w); PST(13, r4);
                CM(r0, r0, w); PST(14, r0); CM(r4, r4, w); PST(15, r4);
#pragma unroll 1
                for (int j = 16; j < 21; j++) { CM(r0, r0, w); PST(j, r0); }
#undef PST
#undef CM
            }
            __syncwarp();
            float KA[2][3][4];
#pragma unroll
            for (int n = 0; n < 24; n++) (&KA[0][0][0])[n] = 0.f;
            const uint32_t ba = pt + (lane & 7) * PT_PITCH + (lane >> 3) * 16, pa_ = pt + 24 * PT_PITCH + q * 16;
            const float gf = (float)g;
            uint4 pv[2]; cf en[2];
#pragma unroll
            for (int m = 0; m < 2; m++) { pv[m] = lds128(pa_ + m * 64); en[m] = cexp2(gf * __uint_as_float(pv[m].x), gf * __uint_as_float(pv[m].y)); }
#pragma unroll 1
            for (int k = 0; k < 4; k++) {
                uint32_t bb[3][4];
                uint4 pn[2][2];
#pragma unroll
                for (int i = 0; i < 4; i++) pn[i >> 1][i & 1] = lds128(pa_ + k * 256 + 128 + i * 64);
#pragma unroll
                for (int n = 0; n < 3; n++) ldsm4(bb[n], ba + n * 8 * PT_PITCH + k * 64);
#pragma unroll
                for (int h = 0; h < 2; h++) {
                    uint32_t a[2][4];
#pragma unroll
                    for (int m = 0; m < 2; m++) {
                        cf e = en[m], z64;
                        z64.x = __uint_as_float(pv[m].z); z64.y = __uint_as_float(pv[m].w);
                        pv[m] = pn[h][m];
                        en[m] = cexp2(gf * __uint_as_float(pv[m].x), gf * __uint_as_float(pv[m].y));
                        a[0][2 * m] = pack2(e.x, e.y); e = cmul(e, z64); a[0][2 * m + 1] = pack2(e.x, e.y); e = cmul(e, z64);
                        a[1][2 * m] = pack2(e.x, e.y); e = cmul(e, z64); a[1][2 * m + 1] = pack2(e.x, e.y);
                    }
#pragma unroll
                    for (int n = 0; n < 3; n++) { mmap(KA[0][n], a[0], bb[n] + 2 * h); mmap(KA[1][n], a[1], bb[n] + 2 * h); }
                }
            }
            float (*KG)[4] = KA[0];
            const uint32_t sw = sb + SM_XS + warp * 1536 + lane * 16;
#define F4(v) make_uint4(fbits(v[0]), fbits(v[1]), fbits(v[2]), fbits(v[3]))
            if (mh) {
#pragma unroll
                for (int n = 0; n < 3; n++) { sts128(sw + n * 512, F4(KA[0][n])); KG[n][0] = KA[1][n][0]; KG[n][1] = KA[1][n][1]; KG[n][2] = KA[1][n][2]; KG[n][3] = KA[1][n][3]; }
            } else {
#pragma unroll
                for (int n = 0; n < 3; n++) sts128(sw + n * 512, F4(KA[1][n]));
            }
            bar_sync(5, 384);
            if (tid == 0) {
                fence_async_global();
                asm volatile("cp.async.bulk.shared::cluster.global.mbarrier::complete_tx::bytes [%0], [%1], 8192, [%2];" ::"r"(sb + SM_ST), "l"(G.stats0), "r"(BAR(B_ST)) : "memory");
            }
#pragma unroll
            for (int n = 0; n < 3; n++) {
                const uint4 v = lds128(sw + (mh ? -1536 : 1536) + n * 512);
                KG[n][0] += __uint_as_float(v.x); KG[n][1] += __uint_as_float(v.y); KG[n][2] += __uint_as_float(v.z); KG[n][3] += __uint_as_float(v.w);
            }
            if (mh == 0 && lane == 0) KG[0][0] += blo(dsk);
#pragma unroll
            for (int n = 0; n < 3; n++)
#pragma unroll
                for (int e = 0; e < 2; e++) {
                    const uint32_t a = sa_[n][e], v = pack2(KG[n][e], KG[n][2 + e]);
                    const bool ok0 = n < 2 || q < 2 || (e == 0 && q == 2 && mh == 0), ok1 = n < 2 || q < 2;
                    if (ok0) { sts16(a, v); sts16(a + 6, v); }
                    if (ok1) { sts16(a + 32, v >> 16); sts16(a + 38, v >> 16); }
                }
        }
        ep += 1;
        bar_sync(1, 256);
        {
            const int o = g - 2 * q;
            const uint32_t wd = sb + SM_WD + w4 * WD_B + 4 * o;
            const uint32_t sel0 = (o >= 0 ? 0x54u : 0x10u) | (o >= 1 ? 0x7600u : 0x3200u);
            const uint32_t oz = lds32(sb + SM_UW + 4 * lane);
            uint32_t ub = sb + SM_UW + w4 * UW_B + 160 * q + 8 * g;
            uint32_t dep = sb + SM_DEP + w4 * 512 + lane * 16;
            const float zero4[4] = {0.f, 0.f, 0.f, 0.f};
            uint32_t A[32][4], f[9][2];
#define LT(T, h) lds32(wd + 4 * ((T) + 8 * (h)))
#define QUAD(Q, a0, a1, a2, a3, id) { Q[0] = a0; Q[1] = a1; Q[2] = cpy(a2, oz, 4 * (id) + 101); Q[3] = cpy(a3, oz, 4 * (id) + 103); }
#define QF(Q, X, L, id) QUAD(Q, X[2 * (L)], X[2 * (L) + 1], (L) ? X[(L) ? 2 * (L) - 1 : 0] : 0u, X[2 * (L)], 16 * (id) + (L))
#define AN(e, L) A[3 * (e) + (L)]
#define AM(e, L) A[24 + 2 * (e) + (L) - 3]
#define A0(a) A[a]
#define A4(a) A[11 + (a)]
#define LF(k) { const uint2 v_ = lds64(ub + (8 - (k)) * 8); f[k][0] = v_.x; f[k][1] = v_.y; }
#define SUM3(d, a, c, e) { d[0] = hadd2(hadd2(f[a][0], f[c][0]), f[e][0]); d[1] = hadd2(hadd2(f[a][1], f[c][1]), f[e][1]); }
#define SUMX(d, p, a, c) { d[0] = hadd2(p[0], hadd2(f[a][0], f[c][0])); d[1] = hadd2(p[1], hadd2(f[a][1], f[c][1])); }
            if (s) {
                {
                    const uint32_t sel1 = (o >= 1 ? 0x54u : 0x10u) | (o >= 2 ? 0x7600u : 0x3200u);
                    uint32_t T0[10], T4[10], X[10];
#pragma unroll
                    for (int h = 0; h < 10; h++) { T0[h] = LT(T0o, h); T4[h] = LT(T4o, h); }
#pragma unroll
                    for (int L = 0; L < 3; L++) { QF(AN(2, L), T0, L, 0) QF(AN(6, L), T4, L, 1) }
#pragma unroll
                    for (int L = 3; L < 5; L++) { QF(AM(1, L), T0, L, 0) QF(AM(3, L), T4, L, 1) }
#pragma unroll
                    for (int k = 0; k < 2; k++) {
#pragma unroll
                        for (int h = 0; h < 9; h++) X[h] = LT(k ? T2o : TM2o, h);
                        X[8] = prmt(X[8], T0[8], k ? sel0 : sel1); X[9] = cpy(T0[9], oz, 11 + 2 * k);
#pragma unroll
                        for (int L = 0; L < 3; L++) QF(AN(4 * k, L), X, L, 2 + k)
#pragma unroll
                        for (int L = 3; L < 5; L++) QF(AM(2 * k, L), X, L, 2 + k)
                    }
#pragma unroll
                    for (int k = 0; k < 4; k++) {
#pragma unroll
                        for (int h = 0; h < 5; h++) X[h] = LT(k == 0 ? TM1o : k == 1 ? T1o : k == 2 ? T3o : T5o, h);
                        X[4] = prmt(X[4], k < 2 ? T0[4] : T4[4], k ? sel0 : sel1); X[5] = cpy(k < 2 ? T0[5] : T4[5], oz, 19 + 2 * k);
#pragma unroll
                        for (int L = 0; L < 3; L++) QF(AN(2 * k + 1, L), X, L, 4 + k)
                    }
                }
                float Pa[5][4], Ra[3][4];
                uint32_t u3[2];
                mbar_wait(BAR(B_UB));
                LF(1) LF(2)
                mmar(Pa[1], zero4, AN(0, 1), f[1]); mmar(Pa[2], zero4, AN(0, 2), f[1]);
                mmar(Pa[3], zero4, AM(0, 3), f[1]); mmar(Pa[4], zero4, AM(0, 4), f[1]);
                mmar(Ra[1], zero4, AN(1, 1), f[2]); mmar(Ra[2], zero4, AN(1, 2), f[2]);
                mmap(Pa[3], AM(1, 3), f[2]); mmap(Pa[4], AM(1, 4), f[2]);
                uint32_t fb[9][2], nb = BAR(B_NEAR);
#define LOADB(F, off) _Pragma("unroll") for (int k = 1; k < 9; k++) { const uint2 v_ = lds64(ub + (off) + (8 - k) * 8); F[k][0] = v_.x; F[k][1] = v_.y; }
#define DEPOSIT(off) { sts128(dep + (off) * 2048, make_uint4(fbits(Pa[0][0] + Ra[0][0]), fbits(Pa[0][1] + Ra[0][1]), fbits(Pa[0][2] + Ra[0][2]), fbits(Pa[0][3] + Ra[0][3]))); \
                    __syncwarp(); if (lane == 0) mbar_arrive(nb + 8 * (off)); }
#define NEAR(f) { SUM3(u3, 2, 4, 3) \
                    mmar(Pa[0], Pa[1], AN(0, 0), f[1]); mmar(Pa[1], Pa[2], AN(0, 1), f[1]); mmar(Pa[2], Pa[3], AN(0, 2), f[1]); \
                    mmar(Pa[3], Pa[4], AM(0, 3), f[1]); mmar(Pa[4], zero4, AM(0, 4), f[1]); \
                    mmar(Ra[0], Ra[1], AN(1, 0), f[2]); mmar(Ra[1], Ra[2], AN(1, 1), f[2]); mmar(Ra[2], zero4, AN(1, 2), f[2]); \
                    mmap(Pa[0], AN(2, 0), f[3]); mmap(Pa[1], AN(2, 1), f[3]); mmap(Pa[2], AN(2, 2), f[3]); \
                    mmap(Pa[3], AM(1, 3), u3); mmap(Pa[4], AM(1, 4), u3); \
                    SUM3(u3, 6, 8, 7) \
                    mmap(Ra[0], AN(3, 0), f[4]); mmap(Ra[1], AN(3, 1), f[4]); mmap(Ra[2], AN(3, 2), f[4]); \
                    mmap(Pa[0], AN(4, 0), f[5]); mmap(Pa[1], AN(4, 1), f[5]); mmap(Pa[2], AN(4, 2), f[5]); \
                    mmap(Ra[0], AN(5, 0), f[6]); \
                    mmap(Pa[3], AM(2, 3), f[5]); mmap(Pa[4], AM(2, 4), f[5]); \
                    mmap(Pa[0], AN(6, 0), f[7]); mmap(Ra[1], AN(5, 1), f[6]); \
                    mmap(Ra[0], AN(7, 0), f[8]); mmap(Ra[2], AN(5, 2), f[6]); \
                    mmap(Pa[1], AN(6, 1), f[7]); mmap(Pa[2], AN(6, 2), f[7]); \
                    mmap(Pa[3], AM(3, 3), u3); mmap(Pa[4], AM(3, 4), u3); \
                    mmap(Ra[1], AN(7, 1), f[8]); mmap(Ra[2], AN(7, 2), f[8]); }
                LOADB(f, 640)
#pragma unroll 1
                for (int sg = 3; sg < 5; sg++) {
#pragma unroll 1
                    for (int i = 0; i < sg; i++) {
                        LOADB(fb, 1280)
                        NEAR(f)
                        LOADB(f, 1920)
                        DEPOSIT(0)
                        { uint32_t (*f)[2] = fb; NEAR(f) }
                        DEPOSIT(1)
                        ub += 1280; dep += 4096; nb += 16;
                    }
                    mbar_wait(BAR(B_UB + 1));
                }
                LOADB(fb, 1280)
                mmar(Pa[0], Pa[1], AN(0, 0), f[1]); mmar(Ra[0], Ra[1], AN(1, 0), f[2]);
#pragma unroll
                for (int e = 0; e < 8; e += 2) {
                    mmap(Pa[2], AN(e, 1), f[e + 1]); mmap(Ra[2], AN(e + 1, 1), f[e + 2]);
                    if (e) { mmap(Pa[0], AN(e, 0), f[e + 1]); mmap(Ra[0], AN(e + 1, 0), f[e + 2]); mmap(Pa[4], AN(e, 0), fb[e + 1]); mmap(Pa[3], AN(e + 1, 0), fb[e + 2]); }
                    else { mmar(Pa[4], zero4, AN(0, 0), fb[1]); mmar(Pa[3], zero4, AN(1, 0), fb[2]); }
                }
                DEPOSIT(0)
#pragma unroll
                for (int i = 0; i < 4; i++) { Pa[0][i] = Pa[2][i] + Pa[4][i]; Ra[0][i] = Ra[2][i] + Pa[3][i]; }
                DEPOSIT(1)
#undef LOADB
#undef DEPOSIT
#undef NEAR
            } else {
                {
                    const int rho = wt & 7, hh = (wt >> 3) & 1;
                    mbar_wait(BAR(B_MOD));
                    uint4 mo = lds128(sb + SM_OWN);
                    const uint32_t tg = ep << 31;
                    mo.z ^= tg | (tg >> 16); mo.w ^= tg | (tg >> 16);
                    mbar_wait(BAR(B_ST));
#pragma unroll 1
                    for (int blk = wt >> 4; blk < 16; blk += 8) {
                        const int t0 = 128 * blk + 32 * hh + rho - 5, e0 = t0 < 0 ? 8 : 0, e9 = t0 >= 2048 - 96 ? 88 : 96;
#define ROW(i) ((i) == 0 ? e0 : (i) == 9 ? e9 : ((i) / 5) * 64 + ((i) % 5) * 8)
                        uint32_t st[10], bad = 0;
#pragma unroll
                        for (int i = 0; i < 10; i++) { st[i] = lds32(sb + SM_ST + (t0 + ROW(i)) * 4); bad = stale(bad, st[i], tg); }
                        for (int it = 0; any(bad >> 31); it++) {
                            bad = 0;
#pragma unroll
                            for (int i = 0; i < 10; i++) { st[i] = ldr32(&G.stats0[t0 + ROW(i)]); bad = stale(bad, st[i], tg); }
                            if (it > SPIN_MAX) __trap();
                        }
                        mbar_wait(BAR(B_XC + (blk >> 3)));
                        const uint32_t uw = sb + SM_UW + (blk + 1) * 640 + hh * 320 + rho * 8, xs = sb + SM_XC + t0 * 16 + 8 * pr;
                        const uint32_t xb = sb + SM_XS + 4 * (160 * blk + 40 * hh + rho - 5);
                        uint32_t hp[2][2];
                        uint2 xv[10];
#pragma unroll
                        for (int i = 0; i < 10; i++) xv[i] = lds64(xs + 1024 * (i & 1) + 128 * (i >> 1));
#pragma unroll
                        for (int i = 0; i < 5; i++) {
                            uint32_t h[2][2];
#pragma unroll
                            for (int u = 0; u < 2; u++) {
                                const uint2 xc = xv[2 * i + u];
                                h[u][0] = hfma2(hnorm2(xc.x, st[5 * u + i]), mo.z, mo.x); h[u][1] = hfma2(hnorm2(xc.y, st[5 * u + i]), mo.w, mo.y);
                                if ((u == 0 && i == 0 && e0) || (u == 1 && i == 4 && e9 == 88)) h[u][0] = h[u][1] = 0u;
                                const uint32_t xd = xb + 320 * u + 32 * i + (i == 4 && rho >= 5 ? 32 : 0);
                                if (i || (u == 0 && (unsigned)t0 < 3u)) { sts32(xd, xc.x); sts32(xd + XS_B, xc.y); }
                            }
#pragma unroll
                            for (int c = 0; c < 4; c++) {
                                const uint32_t sel = (c & 1) ? 0x7632u : 0x5410u;
                                if (i) sts64(uw + c * UW_B + 160 * ((i - 1) >> 1) + 64 * ((i - 1) & 1), prmt(hp[0][c >> 1], h[0][c >> 1], sel), prmt(hp[1][c >> 1], h[1][c >> 1], sel));
                                else if ((unsigned)t0 < 3u) sts32(uw + c * UW_B - 92, prmt(0u, h[0][c >> 1], sel));
                            }
                            hp[0][0] = h[0][0]; hp[0][1] = h[0][1]; hp[1][0] = h[1][0]; hp[1][1] = h[1][1];
                        }
#undef ROW
                        warp_arrive(BAR(B_UB + (blk >> 3)));
                    }
                }
                {
                    const uint32_t selp = (g & 1) ? 0x7610u : 0x1010u;
                    uint32_t T0[33], T4[32];
#pragma unroll
                    for (int h = 9; h < 33; h++) T0[h] = LT(T0o, h);
#pragma unroll
                    for (int h = 9; h < 17; h++) T4[h] = LT(T4o, h);
                    const uint32_t T3x = prmt(T4[16], T0[16], sel0), T5x = prmt(T4[16], LT(T0o + 1, 16), sel0), T5y = LT(T0o + 1, 17);
                    QUAD(A[22], T3x, cpy(T0[17], oz, 11), T4[15], T3x, 2)
                    QUAD(A[23], q ? T5x : (T5x & 0xFFFF0000u), q ? T5y : (T5y & 0xFFFF0000u), T4[15], T5x, 3)
#pragma unroll
                    for (int h = 16; h < 32; h++) {
                        const uint32_t v = prmt(lds32(wd + 4 * (g & 1) + 4 * (T0o + 8 * h)), T0[h], selp);
                        T4[h] = h == 16 ? prmt(T4[16], v, sel0) : v;
                    }
                    QUAD(A[24], 0u, 0u, T0[31], q == 3 ? (T0[32] & 0xFFFF0000u) : 0u, 4)
#pragma unroll
                    for (int L = 5; L < 16; L++) { QF(A0(L - 5), T0, L, 0) QF(A4(L - 5), T4, L, 1) }
                }
                float Fa[12][4], Fx[4];
                uint32_t u3[2], u5[2], u7[2];
                mbar_wait(BAR(B_UB)); mbar_wait(BAR(B_UB + 1));
                LF(0) LF(1) LF(2)
                u5[0] = hadd2(f[1][0], f[2][0]); u5[1] = hadd2(f[1][1], f[2][1]); u7[0] = hadd2(u5[0], f[0][0]); u7[1] = hadd2(u5[1], f[0][1]);
#pragma unroll
                for (int a = 0; a < 11; a++) mmar(Fa[a], zero4, A0(a), a < 4 ? u5 : u7);
                mmar(Fa[11], zero4, A[24], u7);
                ub += 640;
                LF(0) LF(1) LF(2) LF(3) LF(4) LF(5) LF(6) LF(7) LF(8)
                uint32_t xa = sb + SM_XS + (w4 >> 1) * XS_B + 4 * (8 * g + 2 * q + 8 * (g >> 2)), nb = BAR(B_NEAR);
                bf16* xo = G.x2t + (size_t)(4 * b + w4) * 2048 + 8 * g + 2 * q;
                const uint32_t xsel = (w4 & 1) ? 0x7632u : 0x5410u;
                mbar_wait(BAR(B_MOD + 1));
                uint32_t ga = lds32(sb + SM_OWN + 16 + 4 * (w4 >> 1));
                ga = prmt(ga, ga, xsel);
#define FARLOOP(NA) _Pragma("unroll 1") for (int i = 0; i < 4; i++) { \
                    const uint2 x0 = lds64(xa), x1 = lds64(xa + 320); \
                    mbar_wait(nb); \
                    const uint4 nv = lds128(dep); \
                    float y[4] = {__uint_as_float(nv.x), __uint_as_float(nv.y), __uint_as_float(nv.z), __uint_as_float(nv.w)}; \
                    if (NA) { y[0] += Fa[0][0]; y[1] += Fa[0][1]; y[2] += Fa[0][2]; y[3] += Fa[0][3]; } \
                    stg32(xo, hfma2(ga, pack2(y[0], y[1]), prmt(x0.x, x0.y, xsel))); \
                    stg32(xo + 64, hfma2(ga, pack2(y[2], y[3]), prmt(x1.x, x1.y, xsel))); \
                    if (NA == 7 || NA == 3) { __syncwarp(); if (lane == 0 && i == (NA == 7 ? 0 : 3)) mbar_arrive(BAR(B_CONV + (NA == 3))); } \
                    xa += 640; xo += 128; dep += 2048; nb += 8; \
                    if (NA) { \
                        ub += 640; \
                        SUM3(u3, 6, 8, 7) SUM3(u5, 2, 4, 3) SUMX(u5, u5, 1, 5) \
                        if (NA > 3) { SUMX(u7, u5, 0, 6) LF(0) } \
                        LF(1) LF(2) LF(3) LF(4) LF(5) \
                        mmar(Fa[0], Fa[1], A4(0), u3); mmar(Fa[1], Fa[2], A4(1), u3); mmar(Fa[2], Fa[3], A4(2), u3); \
                        if (NA > 3) { \
                            mmar(Fa[3], Fa[4], A[22], f[6]); mmar(Fx, zero4, A[23], f[8]); \
                            _Pragma("unroll") for (int a = 4; a < NA; a++) mmar(Fa[a], Fa[a + 1], A4(a), f[7]); \
                            mmap(Fa[3], A4(3), f[7]); mmap(Fx, A0(3), u5); \
                        } \
                        LF(6) LF(7) LF(8) \
                        mmap(Fa[0], A0(0), u5); mmap(Fa[1], A0(1), u5); mmap(Fa[2], A0(2), u5); \
                        if (NA > 3) { \
                            _Pragma("unroll") for (int a = 4; a < NA; a++) mmap(Fa[a], A0(a), u7); \
                            Fa[3][0] += Fx[0]; Fa[3][1] += Fx[1]; Fa[3][2] += Fx[2]; Fa[3][3] += Fx[3]; \
                        } \
                    } }
                FARLOOP(0) FARLOOP(11)
                FARLOOP(7) FARLOOP(3)
#undef FARLOOP
            }
#undef LT
#undef QUAD
#undef QF
#undef LF
#undef SUM3
#undef SUMX
#undef AN
#undef AM
#undef A0
#undef A4
        }
        {
            float d[4][4];
#pragma unroll
            for (int i = 0; i < 16; i++) (&d[0][0])[i] = 0.f;
            uint32_t wa = sb + SM_W1 + lane * 128 + ((warp ^ (lane & 7)) << 4), ca_ = sb + SM_CBV + 16 * q, va = g < 2 ? ca_ + 1024 * g : sb + SM_ONE;
            const uint32_t vs = g < 2 ? 64 : 0;
            mbar_wait(BAR(B_W1RDY)); mbar_wait(BAR(B_W1FULL));
#pragma unroll 1
            for (int i = 0; i < 4; i++) {
                uint4 v[4], c[4];
                uint32_t bb[4][4];
#pragma unroll
                for (int k = 0; k < 4; k++) { ldsm4t(bb[k], wa + 4096 * k); v[k] = lds128(va); c[k] = lds128(ca_ + 64 * k); va += vs; }
#pragma unroll
                for (int k = 0; k < 4; k++) {
                    mma(d[0], v[k].x, v[k].y, v[k].z, v[k].w, bb[k][0], bb[k][1]); mma(d[1], v[k].x, v[k].y, v[k].z, v[k].w, bb[k][2], bb[k][3]);
                    stsm4t(wa + 4096 * k, hmul2(bb[k][0], c[k].x), hmul2(bb[k][1], c[k].z), hmul2(bb[k][2], c[k].y), hmul2(bb[k][3], c[k].w));
                }
                if (warp == 4) {
#pragma unroll
                    for (int k = 0; k < 4; k++) { mma(d[2], v[k].x, v[k].y, v[k].z, v[k].w, v[k].x, v[k].z); mma(d[3], v[k].x, v[k].y, v[k].z, v[k].w, v[k].y, v[k].w); }
                }
                wa += 16384; ca_ += 256;
            }
            if (g < 4) {
#pragma unroll
                for (int i = 0; i < 2; i++) {
                    const uint32_t w = g < 3 ? split2(d[0][i] + d[1][2 + i]) : 0u;
                    const uint32_t a = sb + SM_U123 + (8 * warp + 2 * q + i) * 16 + 4 * g;
                    sts32(a, prmt(w, w, 0x3232u)); sts32(a + 1024, prmt(w, w, 0x1010u));
                }
            }
            if (warp == 4 && lane < 8) sts64(sb + SM_CONST + 8 * lane, fbits(d[2][0] + d[3][2]), fbits(d[2][1] + d[3][3]));
            fence_async_smem();
            bar_sync(1, 256);
        }

        const int tau = 16 * s + gi, row0 = 64 * tau + 16 * w4 + g;
        float acc[32];
        uint32_t x2p[16];
        {
            float dx[4] = {0.f, 0.f, 0.f, 0.f}, dy[4] = {0.f, 0.f, 0.f, 0.f};
            const uint32_t soff = (32 * (w4 >> 1) + 8 * (w4 & 1) + 16 * ((lane >> 3) & 1) + (lane & 7)) * 128 + ((cs ^ (lane & 7)) << 4);
            const uint32_t xoff = (8 * (lane >> 4) + (lane & 7)) * 128 + (((2 * w4 + ((lane >> 3) & 1)) ^ (lane & 7)) << 4);
            uint32_t ca_ = sb + SM_CBV + 64 * (w4 >> 1) + 8 * (w4 & 1) + 16 * q, va = g < 2 ? ca_ + 1024 * g : sb + SM_ONE;
            int slot = (8 * s) % NSLOT;
#pragma unroll 1
            for (int hf = 0; hf < 8; hf += 4) {
            int sl = slot;
            uint2 cv[4], vv[4];
            uint32_t xv[4][2];
#pragma unroll
            for (int c = 0; c < 4; c++) { cv[c] = lds64(ca_ + 128 * c); vv[c] = lds64(va); va += g < 2 ? 128 : 0; }
            ca_ += 512;
#define CH(c) mbar_wait(BAR(B_FULL + 8 * s + hf + (c))); ldsm2t(xv[c], sb + SM_Q + sl * 8192 + soff); sl = sl == NSLOT - 1 ? 0 : sl + 1;
            CH(0)
            CH(1) CH(2) CH(3)
#undef CH
#pragma unroll
            for (int c = 0; c < 4; c++) {
                const uint32_t y0 = hmul2(xv[c][0], cv[c].x), y1 = hmul2(xv[c][1], cv[c].y);
                mma(dx, xv[c][0], vv[c].x, xv[c][1], vv[c].y, xv[c][0], xv[c][1]);
                mma(dy, y0, vv[c].x, y1, vv[c].y, y0, y1);
            }
            if (hf) {
            const uint32_t red = sb + SM_RED + s * 768;
            if (g < 4) { const uint32_t a = red + g * 128 + q * 32 + w4 * 4; stsf(a, g == 3 ? dx[2] : dy[2]); stsf(a + 16, g == 3 ? dx[3] : dy[3]); }
            if (q == (g >> 1)) { const uint32_t a = red + 512 + g * 16 + w4 * 4; stsf(a, (g & 1) ? dx[1] : dx[0]); stsf(a + 128, (g & 1) ? dy[1] : dy[0]); }
            bar_sync(2 + s, 128);
            if (wt < 8) {
                float S[6];
#pragma unroll
                for (int k = 0; k < 6; k++) {
                    const uint4 v = lds128(red + 128 * k + 16 * wt);
                    S[k] = (__uint_as_float(v.x) + __uint_as_float(v.y)) + (__uint_as_float(v.z) + __uint_as_float(v.w));
                }
                const uint4 k0 = lds128(sb + SM_CONST), k1 = lds128(sb + SM_CONST + 32);
                const float Ccc = __uint_as_float(k0.x), Ccs = __uint_as_float(k0.y), Cc = __uint_as_float(k0.z), Css = __uint_as_float(k1.y), Cs = __uint_as_float(k1.z);
                const float n1 = 1.f / 512.f;
                const float m1 = S[3] * n1, r1 = rsq(fmaxf(fmaf(-m1, m1, S[4] * n1), 0.f) + LN_EPS);
                const float m2 = fmaf(r1, fmaf(-m1, Cc, S[2]), Cs) * n1;
                const float e2 = (r1 * r1 * (S[5] - 2.f * m1 * S[0] + m1 * m1 * Ccc) + 2.f * r1 * fmaf(-m1, Ccs, S[1]) + Css) * n1;
                const float r2 = rsq(fmaxf(fmaf(-m2, m2, e2), 0.f) + LN_EPS), s1 = rcp(r1);
                str128(&G.stats1[64 * tau + 8 * cs + wt], make_uint4(split2(-m1), split2(s1), split2(-m2 * s1), tagf(r1 * r2, ep)));
            }
            __syncwarp();
            }
            WG_FENCE();
#pragma unroll 1
            for (int c = hf; c < hf + 4; c++) {
                const uint32_t da = dlo(SM_Q + slot * 8192, 8192), db = dlo(SM_W1 + c * 8192, 8192);
#pragma unroll
                for (int k = 0; k < 4; k++) wgmma_ss64<1>(acc, da + 128 * k, db + 128 * k, (c | k) != 0);
                slot = slot == NSLOT - 1 ? 0 : slot + 1;
            }
            WG_COMMIT();
            }
#pragma unroll
            for (int n = 0; n < 4; n++) ldsm4t(x2p + 4 * n, sb + SM_Q + ((8 * s + cs) % NSLOT) * 8192 + xoff + n * 2048);
            uint4 s0 = ldr128(&G.stats1[row0]), s1 = ldr128(&G.stats1[row0 + 8]);
            WG_WAIT(0);
            warp_arrive(BAR(B_TILE + s));
            while (any(stale(s0.w ^ ep, s1.w, ep))) { s0 = ldr128(&G.stats1[row0]); s1 = ldr128(&G.stats1[row0 + 8]); }
            {
                const uint32_t a0 = q == 0 ? s0.x : q == 1 ? s0.y : q == 2 ? s0.z : 0u, a1 = q == 0 ? s1.x : q == 1 ? s1.y : q == 2 ? s1.z : 0u;
                WG_FENCE();
                wgmma_rs64<0>(acc, a0, a1, a0, a1, dlo(SM_U123, 1024), 1);
                WG_COMMIT();
            }
            const float al[2] = {__uint_as_float(s0.w), __uint_as_float(s1.w)};
            const float k0[2] = {GK0 * al[0], GK0 * al[1]}, k1[2] = {GK1 * al[0] * al[0] * al[0], GK1 * al[1] * al[1] * al[1]}, kh[2] = {0.5f * al[0], 0.5f * al[1]};
            WG_WAIT(0);
            pin<32>(acc);
            uint32_t gp[2][8];
#pragma unroll
            for (int r = 0; r < 2; r++)
#pragma unroll
                for (int n = 0; n < 8; n++) {
                    const float v0 = acc[4 * n + 2 * r], v1 = acc[4 * n + 2 * r + 1], h0 = kh[r] * v0, h1 = kh[r] * v1;
                    gp[r][n] = pack2(fmaf(h0, gelu_t(v0, k0[r], k1[r]), h0), fmaf(h1, gelu_t(v1, k0[r], k1[r]), h1));
                }
            bf16* go = G.g + (size_t)row0 * 512 + 64 * cs + 8 * q;
#pragma unroll
            for (int r = 0; r < 2; r++) {
                stg128(go + r * 4096, gp[r][0], gp[r][1], gp[r][2], gp[r][3]);
                stg128(go + r * 4096 + 32, gp[r][4], gp[r][5], gp[r][6], gp[r][7]);
            }
            bar_sync(2 + s, 128);
            if (wt == 0) asm volatile("st.release.gpu.global.b32 [%0], %1;" ::"l"(&G.flag[(tau * 8 + cs) * 32]), "r"(ep) : "memory");
            const float r1[2] = {rcp(blo(s0.y) + bhi(s0.y)), rcp(blo(s1.y) + bhi(s1.y))};
            const float c1[2] = {(blo(s0.x) + bhi(s0.x)) * r1[0], (blo(s1.x) + bhi(s1.x)) * r1[1]};
#pragma unroll
            for (int n = 0; n < 8; n++) {
                const uint32_t a = sb + SM_CBV + 128 * cs + 16 * q + vecpos(4 * n), cv = lds32(a), sv = lds32(a + 1024);
#pragma unroll
                for (int r = 0; r < 2; r++) {
                    acc[4 * n + 2 * r] = fmaf(fmaf(blo(x2p[2 * n + r]), r1[r], c1[r]), blo(cv), blo(sv));
                    acc[4 * n + 2 * r + 1] = fmaf(fmaf(bhi(x2p[2 * n + r]), r1[r], c1[r]), bhi(cv), bhi(sv));
                }
            }
        }
        {
            mbar_wait(BAR(B_W2FULL)); mbar_wait(BAR(B_W2FULL + 1)); mbar_wait(BAR(B_W2FULL + 2)); mbar_wait(BAR(B_W2FULL + 3));
            int slot = (16 + 8 * s) % NSLOT;
#pragma unroll 1
            for (int c = 0; c < 8; c++) {
                mbar_wait(BAR(B_FULL + 16 + 8 * s + c));
                const uint32_t da = dlo(SM_Q + slot * 8192, 16), db = dlo(SM_W2 + c * 8192, 8192);
                WG_FENCE();
#pragma unroll
                for (int k = 0; k < 4; k++) wgmma_ss64<0>(acc, da + 2 * k, db + 128 * k, 1);
                WG_COMMIT();
                slot = slot == NSLOT - 1 ? 0 : slot + 1;
            }
            WG_WAIT(0);
            pin<32>(acc);
            warp_arrive(BAR(B_TILE + 2 + s));
            bf16* xo = G.x1 + (size_t)row0 * 512 + 64 * cs + 8 * q;
            float sm[2] = {0.f, 0.f}, sq[2] = {0.f, 0.f};
#pragma unroll
            for (int r = 0; r < 2; r++)
#pragma unroll
                for (int h = 0; h < 2; h++) {
                    const float* a = acc + 16 * h + 2 * r;
                    stg128(xo + r * 4096 + 32 * h, pack2(a[0], a[1]), pack2(a[4], a[5]), pack2(a[8], a[9]), pack2(a[12], a[13]));
                }
#pragma unroll
            for (int i = 0; i < 32; i++) { sm[(i >> 1) & 1] += acc[i]; sq[(i >> 1) & 1] = fmaf(acc[i], acc[i], sq[(i >> 1) & 1]); }
#pragma unroll
            for (int r = 0; r < 2; r++) { sm[r] += shx(sm[r], 1); sq[r] += shx(sq[r], 1); sm[r] += shx(sm[r], 2); sq[r] += shx(sq[r], 2); }
            if (q < 2) G.stats2[2048 * cs + row0 + 8 * q] = q ? make_float2(sm[1], sq[1]) : make_float2(sm[0], sq[0]);
            bar_sync(2 + s, 128);
            if (wt == 0) asm volatile("st.release.gpu.global.b32 [%0], %1;" ::"l"(&G.flag[((32 + tau) * 8 + cs) * 32]), "r"(ep) : "memory");
#pragma unroll
            for (int n = 0; n < 8; n++) {
                const float2 gv = ldsf2(sb + SM_GB + (8 * n + 2 * q) * 4);
#pragma unroll
                for (int r = 0; r < 2; r++) {
                    acc[4 * n + 2 * r] = fmaf(gv.x, acc[4 * n + 2 * r], blo(x2p[2 * n + r]));
                    acc[4 * n + 2 * r + 1] = fmaf(gv.y, acc[4 * n + 2 * r + 1], bhi(x2p[2 * n + r]));
                }
            }
        }
        uint32_t H[56];
        float hr[2];
        const uint32_t hbuf = sb + SM_H + (s ? 0 : 28672) + wt * 16, rb0 = mapa(bar0, pr ^ 1);
        {
            float e[112];
            mbar_wait(BAR(B_SEEN + s));
            const float2* sp = G.stats2 + 4096 * q + row0;
            const uint2 p0 = ldr64(sp), p1 = ldr64(sp + 8), p2 = ldr64(sp + 2048), p3 = ldr64(sp + 2056);
            int slot = (32 + 8 * s) % NSLOT;
#pragma unroll 1
            for (int c = 0; c < 8; c++) {
                mbar_wait(BAR(B_FULL + 32 + 8 * s + c));
                mbar_wait(BAR(B_WFULL + c));
                const uint32_t da = dlo(SM_Q + slot * 8192, 16), db = dlo(wstage(c), 2048);
                WG_FENCE();
#pragma unroll
                for (int k = 0; k < 4; k++) wgmma_ss224(e, da + 2 * k, db + 64 * (k & 1) + 896 * (k >> 1), (c | k) != 0);
                WG_COMMIT();
                if (c) {
                    WG_WAIT(1); __syncwarp();
                    if (lane == 0) {
                        mbar_arrive(BAR(B_WEMPTY + c - 1));
                        if (!s) mbar_arrive(BAR(B_EMPTY + c - 1));
                        else if (c == 4) mbar_arrive_remote(rb0 + 8 * B_HFREE);
                    }
                }
                slot = slot == NSLOT - 1 ? 0 : slot + 1;
            }
            float sm[2] = {__uint_as_float(p0.x) + __uint_as_float(p2.x), __uint_as_float(p1.x) + __uint_as_float(p3.x)};
            float sq[2] = {__uint_as_float(p0.y) + __uint_as_float(p2.y), __uint_as_float(p1.y) + __uint_as_float(p3.y)};
            float k0[2], k1[2];
            uint32_t am[2];
#pragma unroll
            for (int r = 0; r < 2; r++) {
                sm[r] += shx(sm[r], 1); sq[r] += shx(sq[r], 1); sm[r] += shx(sm[r], 2); sq[r] += shx(sq[r], 2);
                const float m = sm[r] * (1.f / 512.f), r3 = rsq(fmaxf(fmaf(-m, m, sq[r] * (1.f / 512.f)), 0.f) + LN_EPS);
                k0[r] = GK0 * r3; k1[r] = GK1 * r3 * r3 * r3; hr[r] = 0.5f * r3;
                am[r] = q < 2 ? split2(-m) : 0u;
            }
            const uint32_t ka = sb + SM_RED + s * 768 + (wt >> 2) * 8;
            sts64(ka, fbits(k1[0]), fbits(k1[1]));
            mbar_wait(BAR(B_U4));
            WG_FENCE();
            wgmma_rs224(e, am[0], am[1], 0u, 0u, dlo(SM_U4, 0), 1);
            WG_COMMIT();
            WG_WAIT(0);
            pin<112>(e);
            __syncwarp();
            if (lane == 0) { mbar_arrive(BAR(B_WEMPTY + 7)); if (!s) mbar_arrive_remote(rb0 + 8 * (B_HFREE + 1)); }
            mbar_wait_cluster(BAR(B_HFREE + s));
#define SENDH(j) asm volatile("st.async.weak.shared::cluster.mbarrier::complete_tx::bytes.v4.b32 [%0], {%1,%2,%3,%4}, [%5];" \
            ::"r"(hbuf + (rb0 - bar0) + (j) * 2048), "r"(H[4 * (j)]), "r"(H[4 * (j) + 1]), "r"(H[4 * (j) + 2]), "r"(H[4 * (j) + 3]), "r"(rb0 + 8 * (B_HFULL + s)) : "memory")
#define GELU(k, k1) { \
                _Pragma("unroll") for (int i = 0; i < 4; i++) { \
                    const float v0 = e[8 * k + 2 * i], v1 = e[8 * k + 2 * i + 1]; \
                    H[4 * k + i] = pack2(fmaf(v0, gelu_t(v0, k0[i & 1], k1[i & 1]), v0), fmaf(v1, gelu_t(v1, k0[i & 1], k1[i & 1]), v1)); \
                } }
            float ka_[2], kb_[2];
#define RL(d) { const float2 t_ = ldsf2(ka); d[0] = t_.x; d[1] = t_.y; }
            RL(ka_) GELU(0, k1) GELU(1, k1) SENDH(0); RL(kb_) GELU(2, ka_) GELU(3, ka_) SENDH(1); SENDH(2); RL(ka_)
            GELU(4, kb_) GELU(5, kb_) SENDH(3); RL(kb_) GELU(6, ka_) GELU(7, ka_) SENDH(4); SENDH(5); RL(ka_)
            GELU(8, kb_) GELU(9, kb_) SENDH(6); RL(kb_) GELU(10, ka_) GELU(11, ka_) SENDH(7); SENDH(8);
            GELU(12, kb_) GELU(13, kb_)
#undef RL
#undef GELU
        }
        {
            float X[32], Y[32];
            uint32_t Hp[56];
            uint4* pdst = G.part + (size_t)((gi * 8 + 4 * pr) * 6 + s) * 512 + wt;
#define TILE(D, A, j, first) { mbar_wait(BAR(B_WFULL + 8 + (j))); WG_FENCE(); \
            _Pragma("unroll") for (int k = 0; k < 14; k++) wgmma_rs64<1>(D, A[4 * k], A[4 * k + 1], A[4 * k + 2], A[4 * k + 3], dlo(wstage(j), 8192) + 128 * k, !(first) || k != 0); \
            WG_COMMIT(); if ((j) && (j) != 5) WG_WAIT(1); if ((j) && (j) < 5) warp_arrive(BAR(B_WEMPTY + 7 + (j))); }
#define SEND(D, st_) { pin<32>(D); uint4* pd = pdst + (((pa + (st_)) & 3) * 6 + 2 * ((st_) - 1)) * 512; \
            _Pragma("unroll") for (int v = 0; v < 4; v++) str128(pd + 128 * v, make_uint4(tagw(pack2(D[8 * v], D[8 * v + 1]), ep), pack2(D[8 * v + 2], D[8 * v + 3]), \
                                                                 pack2(D[8 * v + 4], D[8 * v + 5]), pack2(D[8 * v + 6], D[8 * v + 7]))); }
            pinu<56>(H);
            TILE(X, H, 0, true)
            SENDH(9); SENDH(10); SENDH(11); SENDH(12); SENDH(13);
            TILE(Y, H, 1, true)
            mbar_wait_cluster(BAR(B_HFULL + s));
#pragma unroll
            for (int k = 0; k < 14; k++) {
                const uint4 v = lds128(hbuf + k * 2048); Hp[4 * k] = v.x; Hp[4 * k + 1] = v.y; Hp[4 * k + 2] = v.z; Hp[4 * k + 3] = v.w;
                if (k < 8) sts128(hbuf + k * 2048, make_uint4(__float_as_uint(acc[4 * k]), __float_as_uint(acc[4 * k + 1]), __float_as_uint(acc[4 * k + 2]), __float_as_uint(acc[4 * k + 3])));
            }
            pinu<56>(Hp);
            TILE(X, Hp, 2, false)
            TILE(Y, Hp, 3, false)
            SEND(X, 1)
            TILE(X, H, 4, true)
            SEND(Y, 2)
            TILE(X, Hp, 5, false)
            TILE(Y, H, 6, true)
            SEND(X, 3)
            TILE(Y, Hp, 7, false)
            const uint4* psrc = pdst + pa * 6 * 512;
            uint4 pv[12];
            uint32_t bad;
            do {
                bad = 0;
#pragma unroll
                for (int i = 0; i < 12; i++) pv[i] = ldr128(psrc + (i >> 2) * 1024 + (i & 3) * 128);
#pragma unroll
                for (int i = 0; i < 12; i++) bad = stale(bad, pv[i].x, ep);
            } while (any(bad));
#pragma unroll
            for (int v = 0; v < 4; v++) {
                const uint32_t a[4] = {pv[v].x, pv[v].y, pv[v].z, pv[v].w}, c[4] = {pv[4 + v].x, pv[4 + v].y, pv[4 + v].z, pv[4 + v].w},
                               d[4] = {pv[8 + v].x, pv[8 + v].y, pv[8 + v].z, pv[8 + v].w};
#pragma unroll
                for (int i = 0; i < 4; i++) {
                    const float2 gv = ldsf2(sb + SM_GB + (16 * v + 8 * (i >> 1) + 2 * q) * 4);
                    const int j = 8 * v + 2 * i;
                    if (!(i & 1)) {
                        const uint4 t = lds128(hbuf + (2 * v + (i >> 1)) * 2048);
                        acc[j] = __uint_as_float(t.x); acc[j + 1] = __uint_as_float(t.y); acc[j + 2] = __uint_as_float(t.z); acc[j + 3] = __uint_as_float(t.w);
                    }
                    X[j] = gv.x * hr[i & 1]; X[j + 1] = gv.y * hr[i & 1];
                    acc[j] = fmaf(X[j], blo(a[i]) + blo(c[i]) + blo(d[i]), acc[j]);
                    acc[j + 1] = fmaf(X[j + 1], bhi(a[i]) + bhi(c[i]) + bhi(d[i]), acc[j + 1]);
                }
            }
            WG_WAIT(0);
            pin<32>(Y);
            const uint32_t stg = sb + SM_Q + warp * 2048;
            const int srow = (lane & 7) + 8 * ((lane >> 3) & 1);
#pragma unroll
            for (int n2 = 0; n2 < 4; n2++) {
                uint32_t o[4];
#pragma unroll
                for (int i = 0; i < 4; i++) { const int j = 8 * n2 + 2 * i; o[i] = pack2(fmaf(X[j], Y[j], acc[j]), fmaf(X[j + 1], Y[j + 1], acc[j + 1])); }
                stsm4(stg + srow * 128 + (((2 * n2 + (lane >> 4)) ^ (lane & 7)) << 4), o[0], o[1], o[2], o[3]);
            }
            __syncwarp();
            bf16* oo = P.out + (size_t)(64 * tau + 16 * w4 + (lane >> 3)) * 512 + 64 * cs + 8 * (lane & 7);
#pragma unroll
            for (int i = 0; i < 4; i++) {
                const int r = 4 * i + (lane >> 3);
                const uint4 v = lds128(stg + r * 128 + (((lane & 7) ^ (r & 7)) << 4));
                stg128(oo + i * 2048, v.x, v.y, v.z, v.w);
            }
            if (tid == 128) str32(&G.epoch[b], ep);
            warp_arrive(BAR(B_DONE));
#undef TILE
#undef SEND
#undef SENDH
        }
    } else {
        const int at = tid - 256, aw = warp - 8;
        if (aw) asm volatile("barrier.cluster.arrive.relaxed.aligned;" ::: "memory");
        asm volatile("setmaxnreg.dec.sync.aligned.u32 56;");
        uint4 xr[2][4];
        {
            const bf16* p = P.x + (size_t)(16 * b + g) * 512 + 128 * aw + 8 * q;
#pragma unroll
            for (int i = 0; i < 4; i++) { xr[0][i] = ldg128(p + 32 * i); xr[1][i] = ldg128(p + 4096 + 32 * i); }
        }
        const uint32_t cw = ldg32(P.c + 64 * (b & 7) + 2 * lane);
        uint32_t ep = ldr32(&G.epoch[b]);
        const int mcol = 64 * ((b >> 3) & 7) + 512 * (b >> 6);
        if (aw == 0) {
            if (lane == 0) {
#pragma unroll
                for (int i = 0; i < B_EARLY; i++) mbar_init(BAR(i), 1);
#pragma unroll
                for (int i = 0; i < B_EARLY; i++) mbar_expect(BAR(i), i == B_XC ? 24576 : 8192);
                asm volatile("fence.mbarrier_init.release.cluster;" ::: "memory");
            }
            __syncwarp();
            asm volatile("barrier.cluster.arrive.relaxed.aligned;" ::: "memory");
            if (lane == 0) tma2d(sb + SM_WM, &M.m[tmWm], mcol, 64 * (b & 7), BAR(B_WM));
            asm volatile("barrier.cluster.wait.aligned;" ::: "memory");
            if (lane == 0) {
#pragma unroll 1
                for (int i = 0; i < 4; i++) {
                    tma2d_pair(sb + SM_XC + (2 * i + pr) * 4096, &M.m[tmXc], 8 * (b >> 1), 256 * (2 * i + pr), BAR(B_XC + (i == 3)));
                    if (i == 1 || i == 2) tma2d(sb + SM_WM + 8192 * i, &M.m[tmWm], mcol + 512 * (b >> 6) + 512 + 512 * i, 64 * (b & 7), BAR(B_WM + i));
                }
            }
        } else {
            if (lane == 0) {
                uint32_t b0 = BAR(aw == 1 ? B_FULL : aw == 2 ? B_WFULL : B_NEAR);
                const uint32_t b1 = b0 + (aw == 2 ? 320 : 384);
                do {
#pragma unroll
                    for (int k = 0; k < 8; k++) mbar_init(b0 + 8 * k, aw == 3 ? 4 : 1);
                    b0 += 64;
                } while (b0 != b1);
                if (aw == 3) {
#pragma unroll
                    for (int i = 0; i < 4; i++) { mbar_init(BAR(B_W2FULL + i), 1); mbar_expect(BAR(B_W2FULL + i), 16384); }
                }
                if (aw == 2) {
#pragma unroll
                    for (int i = B_WEMPTY; i <= B_DONE; i++) mbar_init(BAR(i), 8);
                    sts128(sb + SM_ONE, make_uint4(0x3F803F80u, 0x3F803F80u, 0x3F803F80u, 0x3F803F80u));
                }
                asm volatile("fence.mbarrier_init.release.cluster;" ::: "memory");
            }
            __syncwarp();
            if (aw == 1) { mbar_expect(BAR(B_FULL + lane), 8192); if (lane < 16) mbar_expect(BAR(B_FULL + 32 + lane), 8192); }
            if (aw == 2 && lane < 22) mbar_expect(BAR(B_WFULL + lane), lane < 18 ? 28672 : lane < 20 ? 65536 : 8192);
        }
        asm volatile("bar.arrive 5, 384;" ::: "memory");
        {
            const float c0 = blo(cw), c1 = bhi(cw);
            sts32(sb + SM_SCV + aw * 128 + vecpos(lane), pack2(__fdividef(c0, 1.f + __expf(-c0)), __fdividef(c1, 1.f + __expf(-c1))));
        }
        {
            float ds[4] = {0.f, 0.f, 0.f, 0.f}, d0[4] = {0.f, 0.f, 0.f, 0.f}, d1[4] = {0.f, 0.f, 0.f, 0.f};
#pragma unroll
            for (int i = 0; i < 4; i++) {
                const uint4 R = xr[0][i], S = xr[1][i];
                mma(ds, R.x, S.x, R.y, S.y, 0x3F803F80u, 0x3F803F80u); mma(d0, R.x, S.x, R.y, S.y, R.x, R.y); mma(d1, R.x, S.x, R.y, S.y, S.x, S.y);
                mma(ds, R.z, S.z, R.w, S.w, 0x3F803F80u, 0x3F803F80u); mma(d0, R.z, S.z, R.w, S.w, R.z, R.w); mma(d1, R.z, S.z, R.w, S.w, S.z, S.w);
            }
            if (q == (g >> 1)) {
                const uint32_t a = sb + SM_ARED + aw * 128 + g * 8;
                sts64(a, __float_as_uint(ds[0]), __float_as_uint((g & 1) ? d0[1] : d0[0]));
                sts64(a + 64, __float_as_uint(ds[2]), __float_as_uint((g & 1) ? d1[3] : d1[2]));
            }
            ep += 1;
            bar_sync(4, 128);
            if (aw == 3 && lane < 16) {
                const uint32_t a = sb + SM_ARED + lane * 8;
                const float2 v0 = ldsf2(a), v1 = ldsf2(a + 128), v2 = ldsf2(a + 256), v3 = ldsf2(a + 384);
                const float m = ((v0.x + v1.x) + (v2.x + v3.x)) * (1.f / 512.f), e2 = ((v0.y + v1.y) + (v2.y + v3.y)) * (1.f / 512.f);
                const float r = rsq(fmaxf(fmaf(-m, m, e2), 0.f) + LN_EPS);
                str32(&G.stats0[16 * b + lane], (pack2(-m, r) & 0x7FFFFFFFu) | (ep << 31));
            }
        }
        if (aw < 3) {
            const uint4 a0 = lds128(sb + SM_SCV + aw * 128 + q * 16), a1 = lds128(sb + SM_SCV + aw * 128 + 64 + q * 16);
            const uint32_t ta = sb + SM_WM + aw * 8192 + lane * 128;
            const int col = mcol + (aw ? 512 * (b >> 6) + 512 + 512 * aw : 0);
            float t0 = 0.f, t1 = 0.f;
            mbar_wait_b(BAR(B_WM + aw));
#pragma unroll 2
            for (int n = 0; n < 8; n++) {
                uint32_t b0[4], b1[4];
                ldsm4t(b0, ta + ((n ^ (lane & 7)) << 4)); ldsm4t(b1, ta + 4096 + ((n ^ (lane & 7)) << 4));
                float du[4] = {0.f, 0.f, 0.f, 0.f}, dl[4] = {0.f, 0.f, 0.f, 0.f};
                mma(du, a0.x, a0.y, a0.z, a0.w, b0[0], b0[1]); mma(dl, a0.x, a0.y, a0.z, a0.w, b0[2], b0[3]);
                mma(du, a1.x, a1.y, a1.z, a1.w, b1[0], b1[1]); mma(dl, a1.x, a1.y, a1.z, a1.w, b1[2], b1[3]);
                if (n == g) { t0 = du[0] + dl[2]; t1 = du[1] + dl[3]; }
            }
            str64(&G.modq[3072 * (b & 7) + col + 2 * lane], tagf(t0, ep), fbits(t1));
            if (at == 64) {
                l2_prefetch(P.w1 + (size_t)b * 2048, 4096); l2_prefetch(P.w2 + (size_t)b * 2048, 4096);
                l2_prefetch(P.w3 + (size_t)b * 7168, 14336); l2_prefetch(P.w4 + (size_t)b * 7168, 14336);
#pragma unroll 1
                for (int i = 0; i < tmCount; i++) asm volatile("prefetch.tensormap [%0];" ::"l"(&M.m[i]) : "memory");
            }
            if (aw == 1 && lane < 16) str128(&G.stats1[1024 * (lane >> 3) + 64 * gi + 8 * cs + (lane & 7)], make_uint4(ep + 1, ep + 1, ep + 1, ep + 1));
        } else {
#pragma unroll 1
            for (int rd = 0; rd < 2; rd++) {
                const int v = rd ? 2 + (lane >> 3) : (lane >> 3) & 1;
                uint4 w; int it = 0;
                do { w = ldr128(&G.modq[3072 * (lane & 7) + 512 * v + 4 * b]); if (++it > SPIN_MAX) __trap(); } while (any(stale(w.x ^ ep, w.z, ep)));
                float t[4] = {__uint_as_float(w.x), __uint_as_float(w.y), __uint_as_float(w.z), __uint_as_float(w.w)};
#pragma unroll
                for (int i = 0; i < 4; i++) { t[i] += shx(t[i], 1); t[i] += shx(t[i], 2); t[i] += shx(t[i], 4); }
                const uint32_t one = (v == 1 || v == 4) ? 0x3F803F80u : 0x80008000u;
                const uint32_t w0 = hadd2(pack2(t[0], t[1]), one), w1 = hadd2(pack2(t[2], t[3]), one);
                const uint32_t wg = __shfl_sync(0xffffffffu, (lane & 1) ? w1 : w0, 24 + (lane >> 4));
                if (!(lane & 7)) {
                    if (v < 3) sts64(sb + SM_OWN + 8 * v, w0, w1);
                    else if (v < 5) str128(&G.modp[2 * b + v - 3], make_uint4(w0, w1, wg, ep));
                }
                warp_arrive(BAR(B_MOD + rd));
            }
        }
        {
            mbar_wait_b(BAR(B_MOD + 1));
            uint4 v[2];
            for (int it = 0;; it++) {
                v[0] = ldr128(&G.modp[at]); v[1] = ldr128(&G.modp[128 + at]);
                if (!any(stale(v[0].w ^ ep, v[1].w, ep))) break;
                if (it > SPIN_MAX) __trap();
                __nanosleep(100);
            }
#pragma unroll
            for (int h = 0; h < 2; h++) {
                const uint32_t vp = sb + SM_CBV + 512 * h + ((at & 1) ? 0 : 1024) + vecpos(at & ~1);
                sts32(vp, v[h].x); sts32(vp + 16, v[h].y);
                if (4 * h + aw == cs) sts64(sb + SM_GB + 8 * lane, v[h].z << 16, v[h].z & 0xFFFF0000u);
            }
            warp_arrive(BAR(B_W1RDY));
        }
        if (aw < 2) {
            const int s = aw, tau = 16 * s + gi, c = lane & 7;
            const int sh = (c & 4 ? 2 : 1) * (c & 2 ? 1 : -1);
            mbar_wait(BAR(B_CONV + s));
            if (lane == 0) asm volatile("red.release.gpu.global.add.u32 [%0], 1;" ::"l"(&G.cnt[(8 * s + (b >> 4)) * 32]) : "memory");
            __syncwarp();
#pragma unroll 1
            for (int ph = 0; ph < 3; ph++) {
                const uint32_t* fp; uint32_t target = ep; bool need = lane < 8;
                if (ph == 0) { fp = &G.cnt[((tau < 18 ? 0 : 8) + c) * 32]; target = 16 * ep; }
                else if (ph == 1) {
                    const int tn = lane < 8 ? tau : tau + (sh > 0 ? 1 : -1);
                    need = lane < 16 && tn >= 0 && tn < 32;
                    fp = &G.flag[((need ? tn : tau) * 8 + c) * 32];
                } else fp = &G.flag[((32 + tau) * 8 + c) * 32];
                const CUtensorMap* tm = &M.m[tmX2 + ph];
                const int n = 16 * ph + 8 * s + c;
                const uint32_t dst = sb + SM_Q + (n % NSLOT) * 8192;
                const int c0 = ph == 0 ? 64 * tau : 64 * c, c1 = ph == 0 ? 64 * c : 64 * tau + (ph == 1 ? sh : 0);
                const uint32_t eb = BAR(n < 32 + NSLOT ? B_TILE + ((n - NSLOT) >> 3) : B_EMPTY + n - 32 - NSLOT);
                bool pend = lane < 8, room = n < NSLOT, seen = ph != 2;
                for (;;) {
                    if (need) need = (int)(ldr32(fp) - target) < 0;
                    if (pend && !room) room = mbar_test(eb);
                    uint32_t m = __ballot_sync(0xffffffffu, need);
                    if (pend && room && !((m >> c) & 0x101)) {
                        fence_acquire(); fence_async_global();
                        tma2d(dst, tm, c0, c1, BAR(B_FULL + n));
                        pend = false;
                    }
                    if (!m && !seen) { fence_acquire(); warp_arrive(BAR(B_SEEN + s)); seen = true; }
                    if (!__any_sync(0xffffffffu, pend)) break;
                    if (!m) __nanosleep(40);
                }
            }
        } else if (aw == 2) {
            if (lane == 0) {
                mbar_wait(BAR(B_UB));
                fence_async_smem();
                tma2d(sb + SM_W1, &M.m[tmW1], 64 * cs, 0, BAR(B_W1FULL));
                tma2d(sb + SM_W1 + 32768, &M.m[tmW1], 64 * cs, 256, BAR(B_W1FULL));
                mbar_wait(BAR(B_CONV + 1));
                fence_async_smem();
#pragma unroll 1
                for (int t = 0; t < 4; t++) {
                    tma5d(sb + SM_W2 + 16384 * t, &M.m[tmW2], 64 * cs, 0, 0, 0, 4 * t, BAR(B_W2FULL + t));
                    mbar_wait(BAR(B_W2FULL + t));
                }
#pragma unroll 1
                for (int t = 0; t < 8; t++) {
                    if (t < 4) { mbar_wait(BAR(B_TILE + (t & 2))); mbar_wait(BAR(B_TILE + (t | 1))); if (t) mbar_wait(BAR(B_WFULL + t - 1)); } else mbar_wait(BAR(B_WEMPTY + t - 4));
                    tma5d(sb + wstage(t), &M.m[tmW3], 0, 0, 8 * t, 0, 7 * fs, BAR(B_WFULL + t));
                    tma5d(sb + wstage(t) + 14336, &M.m[tmW3], 0, 0, 8 * t + 4, 0, 7 * fs, BAR(B_WFULL + t));
                }
#pragma unroll 1
                for (int j = 0; j < 8; j++) {
                    const int jj = (j == 1 || j == 2) ? 3 - j : j;
                    const int c0 = 64 * (4 * pr + ((pa + (jj >> 1) + 1) & 3)), c1 = 224 * (fs ^ (jj & 1));
                    mbar_wait(BAR(B_WEMPTY + 4 + j));
                    tma2d(sb + wstage(j), &M.m[tmW4], c0, c1, BAR(B_WFULL + 8 + j));
                }
            }
        } else {
            if ((sb & 0x3FFFF) != SMEM_BASE) __trap();
            mbar_wait_b(BAR(B_TILE + 2)); mbar_wait_b(BAR(B_TILE + 3));
            if (b < 112) {
                float d0 = 0.f, d1 = 0.f;
#pragma unroll 1
                for (int h = 0; h < 2; h++) {
                    __syncwarp();
                    if (lane == 0) tma2d(sb + SM_W3C, &M.m[tmW3c], 16 * b, 256 * h, BAR(B_W3C + h));
                    mbar_wait_b(BAR(B_W3C + h));
#pragma unroll 8
                    for (int i = 0; i < 64; i++) { const uint32_t w = lds32(sb + SM_W3C + i * 128 + lane * 4); d0 += blo(w); d1 += bhi(w); }
                }
                d0 += shx(d0, 8); d1 += shx(d1, 8); d0 += shx(d0, 16); d1 += shx(d1, 16);
                if (lane < 8) str64(&G.u4[16 * b + 2 * lane], tagf(d0, ep), fbits(d1));
            }
            uint2 uv[4];
            for (int it = 0;; it++) {
                uint32_t bad = 0;
#pragma unroll
                for (int k = 0; k < 4; k++) { uv[k] = ldr64(&G.u4[224 * fs + 2 * min(lane + 32 * k, 111)]); bad = stale(bad, uv[k].x, ep); }
                if (!any(bad)) break;
                if (it > SPIN_MAX) __trap();
                __nanosleep(100);
            }
#pragma unroll
            for (int k = 0; k < 8; k++) {
                const uint32_t v = split2(__uint_as_float((k & 1) ? uv[k >> 1].y : uv[k >> 1].x));
                sts128(sb + SM_U4 + 32 * min(lane + 32 * (k >> 1), 111) + 16 * (k & 1), make_uint4(prmt(v, v, 0x3232u), prmt(v, v, 0x1010u), 0u, 0u));
            }
            fence_async_smem();
            warp_arrive(BAR(B_U4));
            mbar_wait_b(BAR(B_DONE));
        }
    }
}

#undef G

typedef CUresult (*EncodeFn)(CUtensorMap*, CUtensorMapDataType, cuuint32_t, void*, const cuuint64_t*, const cuuint64_t*,
                             const cuuint32_t*, const cuuint32_t*, CUtensorMapInterleave, CUtensorMapSwizzle,
                             CUtensorMapL2promotion, CUtensorMapFloatOOBfill);

void encode(EncodeFn fn, CUtensorMap* m, const void* base, int rank, const cuuint64_t* dim, const cuuint64_t* stride,
            const cuuint32_t* box, CUtensorMapSwizzle sw) {
    const cuuint32_t es[5] = {1, 1, 1, 1, 1};
    fn(m, CU_TENSOR_MAP_DATA_TYPE_BFLOAT16, rank, const_cast<void*>(base), dim, stride, box, es, CU_TENSOR_MAP_INTERLEAVE_NONE,
       sw, CU_TENSOR_MAP_L2_PROMOTION_L2_128B, CU_TENSOR_MAP_FLOAT_OOB_FILL_NONE);
}

}

extern "C" void kernel_launch(void* const* d_in, const int* in_sizes, int n_in, void* d_out, int out_size) {
    (void)in_sizes; (void)n_in; (void)out_size;
    Params P;
    P.x = (const bf16*)d_in[0]; P.Are = (const bf16*)d_in[1]; P.Aim = (const bf16*)d_in[2]; P.Bre = (const bf16*)d_in[3];
    P.Bim = (const bf16*)d_in[4]; P.Cre = (const bf16*)d_in[5]; P.Cim = (const bf16*)d_in[6]; P.logdt = (const bf16*)d_in[7];
    P.dskip = (const bf16*)d_in[8]; P.w1 = (const bf16*)d_in[10]; P.w2 = (const bf16*)d_in[11]; P.w3 = (const bf16*)d_in[12];
    P.w4 = (const bf16*)d_in[13]; P.c = (const bf16*)d_in[14]; P.wmod = (const bf16*)d_in[15]; P.out = (bf16*)d_out;

    void* fnp = nullptr;
    cudaDriverEntryPointQueryResult qr;
    cudaGetDriverEntryPoint("cuTensorMapEncodeTiled", &fnp, cudaEnableDefault, &qr);
    EncodeFn fn = (EncodeFn)fnp;
    cudaFuncSetAttribute(fused_kernel, cudaFuncAttributeMaxDynamicSharedMemorySize, SM_TOTAL);
    void* pgs;
    cudaGetSymbolAddress(&pgs, g_scratch);
    Scratch* gs = P.gs = (Scratch*)pgs;
    const void *px2 = gs->x2t, *pg = gs->g, *px1 = gs->x1;
    Maps M;
    { const cuuint64_t d[2] = {2048, 512}, st[1] = {4096}; const cuuint32_t bx[2] = {64, 64}; encode(fn, &M.m[tmX2], px2, 2, d, st, bx, CU_TENSOR_MAP_SWIZZLE_128B); }
    { const cuuint64_t d[2] = {512, 2048}, st[1] = {1024}; const cuuint32_t bx[2] = {64, 64};
      encode(fn, &M.m[tmG], pg, 2, d, st, bx, CU_TENSOR_MAP_SWIZZLE_128B); encode(fn, &M.m[tmX1], px1, 2, d, st, bx, CU_TENSOR_MAP_SWIZZLE_128B); }
    { const cuuint64_t d[2] = {512, 512}, st[1] = {1024}; const cuuint32_t bx[2] = {64, 256}; encode(fn, &M.m[tmW1], P.w1, 2, d, st, bx, CU_TENSOR_MAP_SWIZZLE_128B); }
    { const cuuint64_t d[5] = {512, 2, 4, 4, 16}, st[4] = {1024, 8192, 2048, 32768}; const cuuint32_t bx[5] = {64, 2, 4, 4, 4};
      encode(fn, &M.m[tmW2], P.w2, 5, d, st, bx, CU_TENSOR_MAP_SWIZZLE_128B); }
    { const cuuint64_t d[5] = {32, 2, 64, 4, 56}, st[4] = {3584, 8 * 3584, 2 * 3584, 64}; const cuuint32_t bx[5] = {32, 2, 4, 4, 7};
      encode(fn, &M.m[tmW3], P.w3, 5, d, st, bx, CU_TENSOR_MAP_SWIZZLE_64B); }
    { const cuuint64_t d[2] = {512, 1792}, st[1] = {1024}; const cuuint32_t bx[2] = {64, 224}; encode(fn, &M.m[tmW4], P.w4, 2, d, st, bx, CU_TENSOR_MAP_SWIZZLE_128B); }
    { const cuuint64_t d[2] = {512, 2048}, st[1] = {1024}; const cuuint32_t bx[2] = {8, 256}; encode(fn, &M.m[tmXc], P.x, 2, d, st, bx, CU_TENSOR_MAP_SWIZZLE_NONE); }
    { const cuuint64_t d[2] = {3072, 512}, st[1] = {6144}; const cuuint32_t bx[2] = {64, 64}; encode(fn, &M.m[tmWm], P.wmod, 2, d, st, bx, CU_TENSOR_MAP_SWIZZLE_128B); }
    { const cuuint64_t d[2] = {1792, 512}, st[1] = {3584}; const cuuint32_t bx[2] = {16, 256}; encode(fn, &M.m[tmW3c], P.w3, 2, d, st, bx, CU_TENSOR_MAP_SWIZZLE_NONE); }

    cudaLaunchConfig_t cfg = {};
    cfg.gridDim = dim3(128); cfg.blockDim = dim3(384); cfg.dynamicSmemBytes = SM_TOTAL; cfg.stream = cudaStreamPerThread;
    cudaLaunchAttribute at[1];
    at[0].id = cudaLaunchAttributeClusterDimension; at[0].val.clusterDim.x = 2; at[0].val.clusterDim.y = 1; at[0].val.clusterDim.z = 1;
    cfg.attrs = at; cfg.numAttrs = 1;
    cudaLaunchKernelEx(&cfg, fused_kernel, P, M);
}
```

```cpp
#include <cuda_runtime.h>
#include <cuda_bf16.h>
#include <cuda.h>
#include <stdint.h>

namespace {

typedef __nv_bfloat16 bf16;

constexpr int SM_W1 = 0, SM_P1 = 65536, SM_Q = 131072, NSLOT = 11, SM_MISC = SM_Q + NSLOT * 8192;
constexpr int PT_PITCH = 272, PT_B = 24 * PT_PITCH + 1024;
constexpr int UW_B = 10880, SM_UW = SM_P1, XS_B = 10304, SM_XS = SM_UW + 4 * UW_B;
constexpr int WD_B = 3104, SM_WD = SM_Q, SM_SCV = SM_WD + 4 * WD_B;
constexpr int SM_ST = SM_Q + 2 * 8192, SM_WM = SM_Q + 4 * 8192, SM_W3C = SM_Q + 10 * 8192, SM_XC = SM_Q + 7 * 8192, SM_DEP = SM_XC;
constexpr int SM_H = SM_Q + 4 * 8192;
constexpr int SM_BAR = SM_MISC;
constexpr int SM_CBV = SM_BAR + 1024;
constexpr int SM_ONE = SM_CBV + 2048;
constexpr int SM_U123 = SM_ONE + 128;
constexpr int SM_GB = SM_U123 + 768;
constexpr int SM_TB = SM_GB + 256;
constexpr int SM_W1C = SM_TB;
constexpr int SM_U4 = SM_TB;
constexpr int SM_RED = SM_TB + 3584;
constexpr int SM_ARED = SM_RED + 1024;
constexpr int SM_OWN = SM_ARED + 1024;
constexpr int SM_CONST = SM_OWN + 64;
constexpr int SM_TS = SM_CONST + 64;
constexpr int SM_TOTAL = SM_TS + 384;
static_assert(SM_XS + 2 * XS_B <= SM_Q, "conv buffers");
static_assert(SM_TOTAL <= 232448, "smem");
constexpr int T0o = 8, T4o = 288, T2o = 432, TM2o = 512, T1o = 592, T3o = 640, T5o = 688, TM1o = 736;
constexpr int B_WM = 0  , B_XC = 3, B_W3C = 4, B_ST = 5, B_MOD = 6  , B_EARLY = 8,
              B_PAIR = 8  , B_W2FULL = 24  , B_W1C = 28, B_W1FULL = 29, B_HFULL = 30  , B_WFULL = 32  , B_X1 = 48  ,
              B_U4 = 64, B_U123 = 65, B_CONST = 66, B_W3D = 67, B_W3F = 68, B_LN3 = 69  ,
              B_NEAR = 71  , B_EMPTY = 87  , B_TILE = 92  , B_CONV = 96  ,
              B_WA = 98  , B_HFREE = 100  , B_W1RDY = 102, B_AUXQ = 103,
              B_WEMPTY = 105  , B_DST = 104, B_DONE = 117, B_WFREE = 118;

constexpr float LN_EPS = 1e-5f;
constexpr int SPIN_MAX = 1 << 20;

struct Scratch {
    bf16 x2t[512 * 2048], x1[2048 * 512], g[2052 * 512];
    bf16 w1s[512 * 512];
    uint4 stats1[32 * 8 * 64 * 2];
    uint2 stats2[2048 * 8];
    uint32_t stats0[2048];
    uint32_t modq[8 * 3072];
    uint4 modp[128 * 2];
    uint32_t u4[1792], u123[6 * 512];
    uint32_t cnt[17 * 32], flag[2 * 32 * 8 * 32], epoch[128];
    uint4 part[16 * 8 * 3 * 2 * 512];
};
__device__ __align__(1024) Scratch g_scratch;

struct Params {
    const bf16 *Are, *Aim, *Bre, *Bim, *Cre, *Cim, *logdt, *dskip, *x, *c;
    Scratch* gs;
    const bf16 *w1, *w2, *w3, *w4, *wmod;
    bf16* out;
};

enum { tmX2, tmG, tmX1, tmWm, tmXc, tmW3c, tmW1c, tmW1, tmW2, tmW3, tmW4, tmCount };
struct Maps { CUtensorMap m[tmCount]; };

__device__ __forceinline__ void mbar_init(uint32_t b, int c) { asm volatile("mbarrier.init.shared::cta.b64 [%0], %1;" ::"r"(b), "r"(c) : "memory"); }
__device__ __forceinline__ void mbar_expect(uint32_t b, int bytes) { asm volatile("mbarrier.arrive.expect_tx.shared::cta.b64 _, [%0], %1;" ::"r"(b), "r"(bytes) : "memory"); }
__device__ __forceinline__ void mbar_arrive(uint32_t b) { asm volatile("mbarrier.arrive.shared::cta.b64 _, [%0];" ::"r"(b) : "memory"); }
__device__ __forceinline__ void mbar_arrive_remote(uint32_t b) { asm volatile("mbarrier.arrive.relaxed.cluster.shared::cluster.b64 _, [%0];" ::"r"(b) : "memory"); }
__device__ __forceinline__ void mbar_wait(uint32_t b) {
    asm volatile("{.reg .pred p; W: mbarrier.try_wait.parity.shared::cta.b64 p, [%0], 0; @!p bra W;}" ::"r"(b) : "memory");
}
__device__ __forceinline__ void mbar_wait_b(uint32_t b) {
    uint32_t ok; int it = 0;
    do {
        asm volatile("{.reg .pred p; mbarrier.try_wait.parity.shared::cta.b64 p, [%1], 0; selp.u32 %0, 1, 0, p;}" : "=r"(ok) : "r"(b) : "memory");
        if (++it > SPIN_MAX) __trap();
    } while (!ok);
}
__device__ __forceinline__ bool any(uint32_t bad) {
    uint32_t r;
    asm volatile("{.reg .pred p; .reg .b32 t; and.b32 t, %1, 1; setp.ne.b32 p, t, 0; vote.sync.any.pred p, p, 0xffffffff; selp.u32 %0, 1, 0, p;}" : "=r"(r) : "r"(bad));
    return r;
}
#define RARE(c) __builtin_expect((c), 0)
#define warp_arrive(b) do { __syncwarp(); if (lane == 0) mbar_arrive(b); } while (0)
__device__ __forceinline__ void bar_sync(int id, int n) { asm volatile("bar.sync %0, %1;" ::"r"(id), "r"(n) : "memory"); }
__device__ __forceinline__ void fence_async_smem() { asm volatile("fence.proxy.async.shared::cta;" ::: "memory"); }
__device__ __forceinline__ void fence_async_global() { asm volatile("fence.proxy.async.global;" ::: "memory"); }
__device__ __forceinline__ uint32_t mapa(uint32_t a, uint32_t r) { uint32_t d; asm("mapa.shared::cluster.u32 %0, %1, %2;" : "=r"(d) : "r"(a), "r"(r)); return d; }

#define ELECT "{.reg .pred p; elect.sync _|p, 0xffffffff; @p "
__device__ __forceinline__ void tma2d_e(uint32_t dst, const CUtensorMap* m, int c0, int c1, uint32_t bar) {
    asm volatile(ELECT "cp.async.bulk.tensor.2d.shared::cluster.global.mbarrier::complete_tx::bytes [%0], [%1, {%3, %4}], [%2];}"
                 ::"r"(dst), "l"(m), "r"(bar), "r"(c0), "r"(c1) : "memory");
}
__device__ __forceinline__ void tma2d_pair_e(uint32_t dst, const CUtensorMap* m, int c0, int c1, uint32_t bar) {
    asm volatile(ELECT "cp.async.bulk.tensor.2d.shared::cluster.global.mbarrier::complete_tx::bytes.multicast::cluster [%0], [%1, {%3, %4}], [%2], %5;}"
                 ::"r"(dst), "l"(m), "r"(bar), "r"(c0), "r"(c1), "h"((unsigned short)3) : "memory");
}
__device__ __forceinline__ void tma3d_e(uint32_t dst, const CUtensorMap* m, int c0, int c1, int c2, uint32_t bar) {
    asm volatile(ELECT "cp.async.bulk.tensor.3d.shared::cluster.global.mbarrier::complete_tx::bytes [%0], [%1, {%3, %4, %5}], [%2];}"
                 ::"r"(dst), "l"(m), "r"(bar), "r"(c0), "r"(c1), "r"(c2) : "memory");
}
__device__ __forceinline__ void bulk_e(uint32_t dst, const void* src, int bytes, uint32_t bar) {
    asm volatile(ELECT "cp.async.bulk.shared::cluster.global.mbarrier::complete_tx::bytes [%0], [%1], %2, [%3];}" ::"r"(dst), "l"(src), "r"(bytes), "r"(bar) : "memory");
}
__device__ __forceinline__ void l2_prefetch_e(const void* p, int bytes) { asm volatile(ELECT "cp.async.bulk.prefetch.L2.global [%0], %1;}" ::"l"(p), "r"(bytes) : "memory"); }

__device__ __forceinline__ uint32_t lds32(uint32_t a) { uint32_t v; asm volatile("ld.shared.b32 %0, [%1];" : "=r"(v) : "r"(a)); return v; }
__device__ __forceinline__ uint2 lds64(uint32_t a) { uint2 v; asm volatile("ld.shared.v2.b32 {%0,%1}, [%2];" : "=r"(v.x), "=r"(v.y) : "r"(a)); return v; }
__device__ __forceinline__ uint4 lds128(uint32_t a) { uint4 v; asm volatile("ld.shared.v4.b32 {%0,%1,%2,%3}, [%4];" : "=r"(v.x), "=r"(v.y), "=r"(v.z), "=r"(v.w) : "r"(a)); return v; }
__device__ __forceinline__ float2 ldsf2(uint32_t a) { uint2 v = lds64(a); return make_float2(__uint_as_float(v.x), __uint_as_float(v.y)); }
__device__ __forceinline__ void sts16(uint32_t a, uint32_t v) { asm volatile("st.shared.b16 [%0], %1;" ::"r"(a), "h"((unsigned short)v) : "memory"); }
__device__ __forceinline__ void sts32(uint32_t a, uint32_t v) { asm volatile("st.shared.b32 [%0], %1;" ::"r"(a), "r"(v) : "memory"); }
__device__ __forceinline__ void sts64(uint32_t a, uint32_t x, uint32_t y) { asm volatile("st.shared.v2.b32 [%0], {%1,%2};" ::"r"(a), "r"(x), "r"(y) : "memory"); }
__device__ __forceinline__ void sts128(uint32_t a, uint4 v) { asm volatile("st.shared.v4.b32 [%0], {%1,%2,%3,%4};" ::"r"(a), "r"(v.x), "r"(v.y), "r"(v.z), "r"(v.w) : "memory"); }
__device__ __forceinline__ void ldsm4(uint32_t* r, uint32_t a) { asm volatile("ldmatrix.sync.aligned.m8n8.x4.shared.b16 {%0,%1,%2,%3}, [%4];" : "=r"(r[0]), "=r"(r[1]), "=r"(r[2]), "=r"(r[3]) : "r"(a)); }
__device__ __forceinline__ void ldsm4t(uint32_t* r, uint32_t a) { asm volatile("ldmatrix.sync.aligned.m8n8.x4.trans.shared.b16 {%0,%1,%2,%3}, [%4];" : "=r"(r[0]), "=r"(r[1]), "=r"(r[2]), "=r"(r[3]) : "r"(a)); }
__device__ __forceinline__ void stsm4t(uint32_t a, uint32_t r0, uint32_t r1, uint32_t r2, uint32_t r3) { asm volatile("stmatrix.sync.aligned.m8n8.x4.trans.shared.b16 [%0], {%1,%2,%3,%4};" ::"r"(a), "r"(r0), "r"(r1), "r"(r2), "r"(r3) : "memory"); }
__device__ __forceinline__ void stsm4(uint32_t a, uint32_t r0, uint32_t r1, uint32_t r2, uint32_t r3) { asm volatile("stmatrix.sync.aligned.m8n8.x4.shared.b16 [%0], {%1,%2,%3,%4};" ::"r"(a), "r"(r0), "r"(r1), "r"(r2), "r"(r3) : "memory"); }

__device__ __forceinline__ uint32_t ldg16(const void* p) { uint32_t v; asm volatile("ld.global.nc.u16 %0, [%1];" : "=r"(v) : "l"(p)); return v; }
__device__ __forceinline__ uint32_t ldg32(const void* p) { uint32_t v; asm volatile("ld.global.nc.b32 %0, [%1];" : "=r"(v) : "l"(p)); return v; }
__device__ __forceinline__ uint4 ldg128(const void* p) { uint4 v; asm volatile("ld.global.nc.L1::no_allocate.v4.b32 {%0,%1,%2,%3}, [%4];" : "=r"(v.x), "=r"(v.y), "=r"(v.z), "=r"(v.w) : "l"(p)); return v; }
__device__ __forceinline__ uint32_t ldr32(const void* p) { uint32_t v; asm volatile("ld.relaxed.gpu.global.b32 %0, [%1];" : "=r"(v) : "l"(p) : "memory"); return v; }
__device__ __forceinline__ uint2 ldr64(const void* p) { uint2 v; asm volatile("{.reg .b64 t; ld.relaxed.gpu.global.b64 t, [%2]; mov.b64 {%0,%1}, t;}" : "=r"(v.x), "=r"(v.y) : "l"(p) : "memory"); return v; }
__device__ __forceinline__ uint4 ldr128(const void* p) { uint4 v; asm volatile("{.reg .b128 t; ld.relaxed.gpu.global.b128 t, [%4]; mov.b128 {%0,%1,%2,%3}, t;}" : "=r"(v.x), "=r"(v.y), "=r"(v.z), "=r"(v.w) : "l"(p) : "memory"); return v; }
__device__ __forceinline__ void str32(void* p, uint32_t v) { asm volatile("st.relaxed.gpu.global.b32 [%0], %1;" ::"l"(p), "r"(v) : "memory"); }
__device__ __forceinline__ void str64(void* p, uint32_t x, uint32_t y) { asm volatile("{.reg .b64 t; mov.b64 t, {%1,%2}; st.relaxed.gpu.global.b64 [%0], t;}" ::"l"(p), "r"(x), "r"(y) : "memory"); }
__device__ __forceinline__ void str128(void* p, uint4 v) { asm volatile("{.reg .b128 t; mov.b128 t, {%1,%2,%3,%4}; st.relaxed.gpu.global.b128 [%0], t;}" ::"l"(p), "r"(v.x), "r"(v.y), "r"(v.z), "r"(v.w) : "memory"); }
__device__ __forceinline__ void stg32(void* p, uint32_t v) { asm volatile("st.global.b32 [%0], %1;" ::"l"(p), "r"(v) : "memory"); }
__device__ __forceinline__ void stg128(void* p, uint32_t x, uint32_t y, uint32_t z, uint32_t w) { asm volatile("st.global.v4.b32 [%0], {%1,%2,%3,%4};" ::"l"(p), "r"(x), "r"(y), "r"(z), "r"(w) : "memory"); }
__device__ __forceinline__ uint32_t fbits(float f) { return __float_as_uint(f); }
__device__ __forceinline__ uint32_t tagw(uint32_t w, uint32_t ep) { uint32_t r; asm("lop3.b32 %0, %1, %2, 1, 0xD8;" : "=r"(r) : "r"(w), "r"(ep)); return r; }
__device__ __forceinline__ uint32_t tagm(uint32_t w, uint32_t ep, uint32_t m) { uint32_t r; asm("lop3.b32 %0, %1, %2, %3, 0xD8;" : "=r"(r) : "r"(w), "r"(ep), "r"(m)); return r; }
__device__ __forceinline__ void red_add_e(uint32_t* p) { asm volatile(ELECT "red.relaxed.gpu.global.add.u32 [%0], 1;}" ::"l"(p) : "memory"); }
__device__ __forceinline__ uint32_t tagf(float f, uint32_t ep) { return tagw(fbits(f), ep); }
__device__ __forceinline__ uint32_t stale(uint32_t bad, uint32_t w, uint32_t ep) { uint32_t r; asm("lop3.b32 %0, %1, %2, %3, 0xF6;" : "=r"(r) : "r"(bad), "r"(w), "r"(ep)); return r; }

__device__ __forceinline__ uint32_t pack2(float lo, float hi) { uint32_t r; asm("cvt.rn.bf16x2.f32 %0, %1, %2;" : "=r"(r) : "f"(hi), "f"(lo)); return r; }
__device__ __forceinline__ float blo(uint32_t v) { return __uint_as_float(v << 16); }
__device__ __forceinline__ float bhi(uint32_t v) { return __uint_as_float(v & 0xFFFF0000u); }
__device__ __forceinline__ float bround(float v) { return blo(pack2(v, 0.f)); }
__device__ __forceinline__ uint32_t hadd2(uint32_t a, uint32_t b) { uint32_t r; asm("add.rn.bf16x2 %0, %1, %2;" : "=r"(r) : "r"(a), "r"(b)); return r; }
__device__ __forceinline__ uint32_t hmul2(uint32_t a, uint32_t b) { uint32_t r; asm("mul.rn.bf16x2 %0, %1, %2;" : "=r"(r) : "r"(a), "r"(b)); return r; }
__device__ __forceinline__ uint32_t hfma2(uint32_t a, uint32_t b, uint32_t c) { uint32_t r; asm("fma.rn.bf16x2 %0, %1, %2, %3;" : "=r"(r) : "r"(a), "r"(b), "r"(c)); return r; }
__device__ __forceinline__ uint32_t hnorm2(uint32_t x, uint32_t s) {
    uint32_t r;
    asm("{.reg .b16 l, h; .reg .b32 a, c; mov.b32 {l, h}, %2; mov.b32 a, {l, l}; mov.b32 c, {h, h}; add.rn.bf16x2 a, %1, a; mul.rn.bf16x2 %0, a, c;}" : "=r"(r) : "r"(x), "r"(s));
    return r;
}
__device__ __forceinline__ uint32_t prmt(uint32_t a, uint32_t b, uint32_t s) { uint32_t r; asm("prmt.b32 %0, %1, %2, %3;" : "=r"(r) : "r"(a), "r"(b), "r"(s)); return r; }
__device__ __forceinline__ float rsq(float v) { float r; asm("rsqrt.approx.ftz.f32 %0, %1;" : "=f"(r) : "f"(v)); return r; }
__device__ __forceinline__ float shx(float v, int m) { return __shfl_xor_sync(0xffffffffu, v, m); }
__device__ __forceinline__ float gelu_t(float v, float k0, float k1) {
    float t;
    asm("tanh.approx.f32 %0, %1;" : "=f"(t) : "f"(v * fmaf(v * k1, v, k0)));
    return t;
}
constexpr float GK0 = 0.7978845608028654f, GK1 = 0.0356774081363001f;
__device__ __forceinline__ uint32_t split2(float c) { const float h = bround(c); return pack2(c - h, h); }
struct cf { float x, y; };
__device__ __forceinline__ cf cmul(cf a, cf b) { cf r; r.x = fmaf(a.x, b.x, -a.y * b.y); r.y = fmaf(a.x, b.y, a.y * b.x); return r; }
__device__ __forceinline__ cf cexp2(float e, float th) {
    float m; asm("ex2.approx.ftz.f32 %0, %1;" : "=f"(m) : "f"(e));
    cf r; r.x = m * __cosf(th); r.y = m * __sinf(th); return r;
}

__device__ __forceinline__ void mma(float* d, uint32_t a0, uint32_t a1, uint32_t a2, uint32_t a3, uint32_t b0, uint32_t b1) {
    asm volatile("mma.sync.aligned.m16n8k16.row.col.f32.bf16.bf16.f32 {%0,%1,%2,%3},{%4,%5,%6,%7},{%8,%9},{%0,%1,%2,%3};"
                 : "+f"(d[0]), "+f"(d[1]), "+f"(d[2]), "+f"(d[3]) : "r"(a0), "r"(a1), "r"(a2), "r"(a3), "r"(b0), "r"(b1));
}
__device__ __forceinline__ void mmap(float* d, const uint32_t* a, const uint32_t* b) { mma(d, a[0], a[1], a[2], a[3], b[0], b[1]); }
__device__ __forceinline__ void mmar(float* d, const float* c, const uint32_t* a, const uint32_t* b) {
    asm volatile("mma.sync.aligned.m16n8k16.row.col.f32.bf16.bf16.f32 {%0,%1,%2,%3},{%4,%5,%6,%7},{%8,%9},{%10,%11,%12,%13};"
                 : "=f"(d[0]), "=f"(d[1]), "=f"(d[2]), "=f"(d[3])
                 : "r"(a[0]), "r"(a[1]), "r"(a[2]), "r"(a[3]), "r"(b[0]), "r"(b[1]), "f"(c[0]), "f"(c[1]), "f"(c[2]), "f"(c[3]));
}
__device__ __forceinline__ uint32_t cpy(uint32_t a, uint32_t z, int k) { return a + z * (uint32_t)k; }

#define WG_FENCE() asm volatile("wgmma.fence.sync.aligned;" ::: "memory")
#define WG_COMMIT() asm volatile("wgmma.commit_group.sync.aligned;" ::: "memory")
#define WG_WAIT(n) asm volatile("wgmma.wait_group.sync.aligned " #n ";" ::: "memory")
template <int N> __device__ __forceinline__ void pin(float* d) {
#pragma unroll
    for (int i = 0; i < N; i++) asm volatile("" : "+f"(d[i])::"memory");
}
template <int N> __device__ __forceinline__ void pinu(uint32_t* d) {
#pragma unroll
    for (int i = 0; i < N; i++) asm volatile("" : "+r"(d[i])::"memory");
}
__device__ __forceinline__ uint64_t desc(uint32_t addr, uint32_t lbo, uint32_t hi = 0x40000040u) {
    uint64_t d;
    asm volatile("mov.b64 %0, {%1, %2};" : "=l"(d) : "r"(((addr & 0x3FFFF) >> 4) + ((lbo >> 4) << 16)), "r"(hi));
    return d;
}
__device__ __forceinline__ void wgmma_ss224(float* d, uint64_t da, uint64_t db, int sd) {
    asm volatile("{.reg .pred p; setp.ne.b32 p, %114, 0;\n"
                 "wgmma.mma_async.sync.aligned.m64n224k16.f32.bf16.bf16 {%0, %1, %2, %3, %4, %5, %6, %7, %8, %9, %10, %11, %12, %13, %14, %15, %16, %17, %18, %19, %20, %21, %22, %23, %24, %25, %26, %27, %28, %29, %30, %31, %32, %33, %34, %35, %36, %37, %38, %39, %40, %41, %42, %43, %44, %45, %46, %47, %48, %49, %50, %51, %52, %53, %54, %55, %56, %57, %58, %59, %60, %61, %62, %63, %64, %65, %66, %67, %68, %69, %70, %71, %72, %73, %74, %75, %76, %77, %78, %79, %80, %81, %82, %83, %84, %85, %86, %87, %88, %89, %90, %91, %92, %93, %94, %95, %96, %97, %98, %99, %100, %101, %102, %103, %104, %105, %106, %107, %108, %109, %110, %111}, %112, %113, p, 1, 1, %115, 1;}"
                 : "+f"(d[0]), "+f"(d[1]), "+f"(d[2]), "+f"(d[3]), "+f"(d[4]), "+f"(d[5]), "+f"(d[6]), "+f"(d[7]),
                   "+f"(d[8]), "+f"(d[9]), "+f"(d[10]), "+f"(d[11]), "+f"(d[12]), "+f"(d[13]), "+f"(d[14]), "+f"(d[15]),
                   "+f"(d[16]), "+f"(d[17]), "+f"(d[18]), "+f"(d[19]), "+f"(d[20]), "+f"(d[21]), "+f"(d[22]), "+f"(d[23]),
                   "+f"(d[24]), "+f"(d[25]), "+f"(d[26]), "+f"(d[27]), "+f"(d[28]), "+f"(d[29]), "+f"(d[30]), "+f"(d[31]),
                   "+f"(d[32]), "+f"(d[33]), "+f"(d[34]), "+f"(d[35]), "+f"(d[36]), "+f"(d[37]), "+f"(d[38]), "+f"(d[39]),
                   "+f"(d[40]), "+f"(d[41]), "+f"(d[42]), "+f"(d[43]), "+f"(d[44]), "+f"(d[45]), "+f"(d[46]), "+f"(d[47]),
                   "+f"(d[48]), "+f"(d[49]), "+f"(d[50]), "+f"(d[51]), "+f"(d[52]), "+f"(d[53]), "+f"(d[54]), "+f"(d[55]),
                   "+f"(d[56]), "+f"(d[57]), "+f"(d[58]), "+f"(d[59]), "+f"(d[60]), "+f"(d[61]), "+f"(d[62]), "+f"(d[63]),
                   "+f"(d[64]), "+f"(d[65]), "+f"(d[66]), "+f"(d[67]), "+f"(d[68]), "+f"(d[69]), "+f"(d[70]), "+f"(d[71]),
                   "+f"(d[72]), "+f"(d[73]), "+f"(d[74]), "+f"(d[75]), "+f"(d[76]), "+f"(d[77]), "+f"(d[78]), "+f"(d[79]),
                   "+f"(d[80]), "+f"(d[81]), "+f"(d[82]), "+f"(d[83]), "+f"(d[84]), "+f"(d[85]), "+f"(d[86]), "+f"(d[87]),
                   "+f"(d[88]), "+f"(d[89]), "+f"(d[90]), "+f"(d[91]), "+f"(d[92]), "+f"(d[93]), "+f"(d[94]), "+f"(d[95]),
                   "+f"(d[96]), "+f"(d[97]), "+f"(d[98]), "+f"(d[99]), "+f"(d[100]), "+f"(d[101]), "+f"(d[102]), "+f"(d[103]),
                   "+f"(d[104]), "+f"(d[105]), "+f"(d[106]), "+f"(d[107]), "+f"(d[108]), "+f"(d[109]), "+f"(d[110]), "+f"(d[111])
                 : "l"(da), "l"(db), "r"(sd), "n"(0));
}
template <int TB> __device__ __forceinline__ void wgmma_rs64(float* d, uint32_t a0, uint32_t a1, uint32_t a2, uint32_t a3, uint64_t db, int sd) {
    asm volatile("{.reg .pred p; setp.ne.b32 p, %37, 0;\n"
                 "wgmma.mma_async.sync.aligned.m64n64k16.f32.bf16.bf16 {%0, %1, %2, %3, %4, %5, %6, %7, %8, %9, %10, %11, %12, %13, %14, %15, %16, %17, %18, %19, %20, %21, %22, %23, %24, %25, %26, %27, %28, %29, %30, %31}, {%32, %33, %34, %35}, %36, p, 1, 1, %38;}"
                 : "+f"(d[0]), "+f"(d[1]), "+f"(d[2]), "+f"(d[3]), "+f"(d[4]), "+f"(d[5]), "+f"(d[6]), "+f"(d[7]),
                   "+f"(d[8]), "+f"(d[9]), "+f"(d[10]), "+f"(d[11]), "+f"(d[12]), "+f"(d[13]), "+f"(d[14]), "+f"(d[15]),
                   "+f"(d[16]), "+f"(d[17]), "+f"(d[18]), "+f"(d[19]), "+f"(d[20]), "+f"(d[21]), "+f"(d[22]), "+f"(d[23]),
                   "+f"(d[24]), "+f"(d[25]), "+f"(d[26]), "+f"(d[27]), "+f"(d[28]), "+f"(d[29]), "+f"(d[30]), "+f"(d[31])
                 : "r"(a0), "r"(a1), "r"(a2), "r"(a3), "l"(db), "r"(sd), "n"(TB));
}
__device__ __forceinline__ void wgmma_rs224(float* d, uint32_t a0, uint32_t a1, uint32_t a2, uint32_t a3, uint64_t db, int sd) {
    asm volatile("{.reg .pred p; setp.ne.b32 p, %117, 0;\n"
                 "wgmma.mma_async.sync.aligned.m64n224k16.f32.bf16.bf16 {%0, %1, %2, %3, %4, %5, %6, %7, %8, %9, %10, %11, %12, %13, %14, %15, %16, %17, %18, %19, %20, %21, %22, %23, %24, %25, %26, %27, %28, %29, %30, %31, %32, %33, %34, %35, %36, %37, %38, %39, %40, %41, %42, %43, %44, %45, %46, %47, %48, %49, %50, %51, %52, %53, %54, %55, %56, %57, %58, %59, %60, %61, %62, %63, %64, %65, %66, %67, %68, %69, %70, %71, %72, %73, %74, %75, %76, %77, %78, %79, %80, %81, %82, %83, %84, %85, %86, %87, %88, %89, %90, %91, %92, %93, %94, %95, %96, %97, %98, %99, %100, %101, %102, %103, %104, %105, %106, %107, %108, %109, %110, %111}, {%112, %113, %114, %115}, %116, p, 1, 1, %118;}"
                 : "+f"(d[0]), "+f"(d[1]), "+f"(d[2]), "+f"(d[3]), "+f"(d[4]), "+f"(d[5]), "+f"(d[6]), "+f"(d[7]),
                   "+f"(d[8]), "+f"(d[9]), "+f"(d[10]), "+f"(d[11]), "+f"(d[12]), "+f"(d[13]), "+f"(d[14]), "+f"(d[15]),
                   "+f"(d[16]), "+f"(d[17]), "+f"(d[18]), "+f"(d[19]), "+f"(d[20]), "+f"(d[21]), "+f"(d[22]), "+f"(d[23]),
                   "+f"(d[24]), "+f"(d[25]), "+f"(d[26]), "+f"(d[27]), "+f"(d[28]), "+f"(d[29]), "+f"(d[30]), "+f"(d[31]),
                   "+f"(d[32]), "+f"(d[33]), "+f"(d[34]), "+f"(d[35]), "+f"(d[36]), "+f"(d[37]), "+f"(d[38]), "+f"(d[39]),
                   "+f"(d[40]), "+f"(d[41]), "+f"(d[42]), "+f"(d[43]), "+f"(d[44]), "+f"(d[45]), "+f"(d[46]), "+f"(d[47]),
                   "+f"(d[48]), "+f"(d[49]), "+f"(d[50]), "+f"(d[51]), "+f"(d[52]), "+f"(d[53]), "+f"(d[54]), "+f"(d[55]),
                   "+f"(d[56]), "+f"(d[57]), "+f"(d[58]), "+f"(d[59]), "+f"(d[60]), "+f"(d[61]), "+f"(d[62]), "+f"(d[63]),
                   "+f"(d[64]), "+f"(d[65]), "+f"(d[66]), "+f"(d[67]), "+f"(d[68]), "+f"(d[69]), "+f"(d[70]), "+f"(d[71]),
                   "+f"(d[72]), "+f"(d[73]), "+f"(d[74]), "+f"(d[75]), "+f"(d[76]), "+f"(d[77]), "+f"(d[78]), "+f"(d[79]),
                   "+f"(d[80]), "+f"(d[81]), "+f"(d[82]), "+f"(d[83]), "+f"(d[84]), "+f"(d[85]), "+f"(d[86]), "+f"(d[87]),
                   "+f"(d[88]), "+f"(d[89]), "+f"(d[90]), "+f"(d[91]), "+f"(d[92]), "+f"(d[93]), "+f"(d[94]), "+f"(d[95]),
                   "+f"(d[96]), "+f"(d[97]), "+f"(d[98]), "+f"(d[99]), "+f"(d[100]), "+f"(d[101]), "+f"(d[102]), "+f"(d[103]),
                   "+f"(d[104]), "+f"(d[105]), "+f"(d[106]), "+f"(d[107]), "+f"(d[108]), "+f"(d[109]), "+f"(d[110]), "+f"(d[111])
                 : "r"(a0), "r"(a1), "r"(a2), "r"(a3), "l"(db), "r"(sd), "n"(0));
}

__device__ __forceinline__ uint32_t vecpos(int kw) { return (kw >> 4) * 64 + (kw & 3) * 16 + ((kw >> 2) & 1) * 8 + ((kw >> 3) & 1) * 4; }

__device__ __forceinline__ uint32_t check(uint32_t bad, uint4 v, uint32_t ep) {
    uint32_t t0, t1;
    asm("lop3.b32 %0, %1, %2, %3, 0x7E;" : "=r"(t0) : "r"(v.x), "r"(v.y), "r"(ep));
    asm("lop3.b32 %0, %1, %2, %3, 0x7E;" : "=r"(t1) : "r"(v.z), "r"(v.w), "r"(ep));
    return bad | t0 | t1;
}
__device__ __forceinline__ uint32_t check_tile(uint32_t a, uint32_t ep) {
    const uint4 t0 = make_uint4(lds32(a), lds32(a + 8192), lds32(a + 16384), lds32(a + 24576));
    const uint4 t1 = make_uint4(lds32(a + 32768), lds32(a + 40960), lds32(a + 49152), lds32(a + 57344));
    return check(check(0, t0, ep), t1, ep);
}
template <int NCH, int CSTEP, bool SHIFT> __device__ __forceinline__ void refetch(uint32_t a, uint32_t ep, const bf16* src) {
    int c = 0;
    do {
        const uint32_t d = a + 8192 * c;
        if (any(lds32(d) ^ ep)) {
#pragma unroll 1
            for (int k = 0; k < 4; k++) sts128((d & ~15u) ^ (16 * k), ldr128(src + 8 * (3 ^ k) + CSTEP * c + (SHIFT ? (c & 4 ? 1024 : 512) * (c & 2 ? 1 : -1) : 0)));
        } else c++;
    } while (c < NCH);
    fence_async_smem();
}
__device__ __forceinline__ bool bar_any(int id, int n, uint32_t bad) {
    uint32_t r;
    asm volatile("{.reg .pred p, q; setp.ne.b32 p, %3, 0; bar.red.or.pred q, %1, %2, p; selp.u32 %0, 1, 0, q;}" : "=r"(r) : "r"(id), "r"(n), "r"(bad & 1) : "memory");
    return any(r);
}

template <bool TAG> __device__ __forceinline__ void store_rows(uint32_t a, bf16* dst, int lane, uint32_t ep) {
    const uint4 v[4] = {lds128(a), lds128((a ^ 64) + 512), lds128(a + 1024), lds128((a ^ 64) + 1536)};
    const uint32_t m0 = (lane & 7) == 3, m1 = (lane & 7) == 7;
#pragma unroll
    for (int i = 0; i < 4; i++) stg128(dst + 2048 * i, TAG ? tagm(v[i].x, ep, m0) : v[i].x, TAG ? tagm(v[i].y, ep, m1) : v[i].y, v[i].z, v[i].w);
}

__device__ __forceinline__ uint32_t wstage(int q) { return (q & 3) * 32768; }

__global__ void __launch_bounds__(384, 1) __cluster_dims__(2, 1, 1)
fused_kernel(const Params P, const __grid_constant__ Maps M)
{
    extern __shared__ __align__(1024) uint8_t smem_raw[];
    const uint32_t sb = __shfl_sync(0xffffffffu, (uint32_t)__cvta_generic_to_shared(smem_raw), 0);
    int tid = threadIdx.x, lane = tid & 31, g = lane >> 2, q = lane & 3, wt = tid & 127;
#define RELANE() { tid = __shfl_sync(0xffffffffu, (int)threadIdx.x, threadIdx.x & 31); lane = tid & 31; g = lane >> 2; q = lane & 3; wt = tid & 127; }
    const int warp = __shfl_sync(0xffffffffu, (int)threadIdx.x >> 5, 0);
    const int pr = blockIdx.x & 1, cl = blockIdx.x >> 1, p7 = ((cl - 36) * 37) >> 8;
    const int pa = cl < 4 ? cl : cl < 36 ? (cl - 4) >> 3 : p7, gi = cl < 4 ? 15 : cl < 36 ? (cl - 4) & 7 : cl - 28 - 7 * p7;
    const int fs = 2 * pa + pr;
    const int cs = 4 * pr + pa;
    const int b = 8 * gi + fs;
    const int mcol = 64 * ((b >> 3) & 7) + 512 * (b >> 6);
    const uint32_t bar0 = sb + SM_BAR;
#define BAR(i) (bar0 + 8 * (i))
#define G (*P.gs)
#define XP 0
#define PACE (!((XP >> (10 + t)) & 1))
#define OWNMOD(rd) { \
        const int v = (rd) ? 2 + (lane >> 3) : (lane >> 3) & 1; \
        uint4 w; int it = 0; \
        do { w = ldr128(&G.modq[3072 * (lane & 7) + 512 * v + 4 * b]); if (++it > SPIN_MAX) __trap(); } while (any(stale(w.x ^ ep, w.z, ep))); \
        float t[4] = {__uint_as_float(w.x), __uint_as_float(w.y), __uint_as_float(w.z), __uint_as_float(w.w)}; \
        _Pragma("unroll") for (int i = 0; i < 4; i++) { t[i] += shx(t[i], 1); t[i] += shx(t[i], 2); t[i] += shx(t[i], 4); } \
        const uint32_t one = v == ((rd) ? 4 : 1) ? 0x3F803F80u : 0x80008000u; \
        const uint32_t w0 = hadd2(pack2(t[0], t[1]), one), w1 = hadd2(pack2(t[2], t[3]), one); \
        sts64(sb + SM_OWN + 8 * v, w0, w1); \
        if (rd) { \
            const uint32_t wg = __shfl_sync(0xffffffffu, (lane & 1) ? w1 : w0, 24 + (lane >> 4)); \
            if (lane == 8 || lane == 16) str128(&G.modp[2 * b + v - 3], make_uint4(w0, w1, wg, ep)); \
        } \
        warp_arrive(BAR(B_MOD + (rd))); }

    uint32_t pAre, pAim, pBre, pBim, pCre, pCim;
    {
        const uint32_t po = b * 512 + 2 * tid;
        asm volatile("{.reg .pred p; setp.lt.s32 p, %12, 256;\n"
                     "@p ld.global.nc.b32 %0, [%6]; @p ld.global.nc.b32 %1, [%7]; @p ld.global.nc.b32 %2, [%8];\n"
                     "@p ld.global.nc.b32 %3, [%9]; @p ld.global.nc.b32 %4, [%10]; @p ld.global.nc.b32 %5, [%11];}"
                     : "=r"(pAre), "=r"(pAim), "=r"(pBre), "=r"(pBim), "=r"(pCre), "=r"(pCim)
                     : "l"(P.Are + po), "l"(P.Aim + po), "l"(P.Bre + po), "l"(P.Bim + po), "l"(P.Cre + po), "l"(P.Cim + po), "r"(tid));
    }
    if (warp < 8) {
        const int s = warp >> 2, w4 = warp & 3;
        asm volatile("barrier.cluster.arrive.relaxed.aligned;" ::: "memory");
        const uint32_t ldt = ldg16(P.logdt + (uint32_t)(4 * b + (warp >> 1))), dsk = ldg16(P.dskip + (uint32_t)(4 * b + (warp >> 1)));
        {
            const uint32_t d = sb + SM_XS + warp * 2048 + (lane >> 3) * 128 + (((lane ^ (lane >> 3)) & 7) << 4);
            const bf16* p = P.x + (uint32_t)((16 * b + (lane >> 3)) * 512 + 64 * warp + 8 * (lane & 7));
#pragma unroll
            for (int i = 0; i < 4; i++) asm volatile("cp.async.cg.shared.global [%0], [%1], 16;" ::"r"((d ^ (64 * (i & 1))) + 512 * i), "l"(p + 2048 * i) : "memory");
        }
        uint32_t ep = ldr32(&G.epoch[b]);
        asm volatile("setmaxnreg.inc.sync.aligned.u32 224;");
        RELANE()
#pragma unroll
        for (int i = 0; i < 3; i++) sts128(sb + SM_WD + (tid + 256 * i) * 16, make_uint4(0, 0, 0, 0));
        sts128((tid & 63) < 40 ? sb + SM_UW + (warp >> 1) * UW_B + (tid & 63) * 16 : sb + SM_WD + (768 + (tid & 7)) * 16, make_uint4(0, 0, 0, 0));
        {
            const int mh = warp & 1;
            uint32_t sa_[3][2];
            {
                const uint32_t wd = sb + SM_WD + (warp >> 1) * WD_B + (16 * mh + g) * 4, sel = 0x4410u + 0x22u * (q & 1);
#define CBW(a, c) ((uint32_t)(4 * (a)) | ((uint32_t)(4 * (c)) << 16))
#define CBS(a, c, d, e) (wd + prmt(q & 2 ? CBW(d, e) : CBW(a, c), 0u, sel))
                sa_[0][0] = CBS(T0o, T2o, T4o, TM2o + 1); sa_[0][1] = CBS(T1o, T3o, T5o, TM1o + 1);
                sa_[1][0] = CBS(T0o + 32, T4o + 32, T0o + 64, T0o + 96); sa_[1][1] = CBS(T2o + 32, TM2o + 33, T4o + 64, T4o + 96);
                sa_[2][0] = wd + 4 * (T0o + 128) + 256 * q; sa_[2][1] = sa_[2][0] + 128;
#undef CBW
#undef CBS
                pinu<6>(&sa_[0][0]);
            }
            const uint32_t pt = sb + SM_W1 + warp * PT_B;
            {
                const float dt = bround(expf(blo(ldt)));
                cf z[2], w[2], r0[2], r2[2], r4[2], t[2];
#pragma unroll
                for (int m = 0; m < 2; m++) {
                    const float a = dt * (m ? bhi(pAre) : blo(pAre)) * 1.4426950408889634f, th = dt * (m ? bhi(pAim) : blo(pAim));
                    const cf z64 = cexp2(64.f * a, 64.f * th);
                    sts128(pt + 24 * PT_PITCH + lane * 32 + m * 16, make_uint4(__float_as_uint(8.f * a), __float_as_uint(8.f * th), __float_as_uint(z64.x), __float_as_uint(z64.y)));
                    z[m] = cexp2(a, -th); w[m] = cexp2(256.f * a, -256.f * th);
                    cf C, B;
                    C.x = m ? bhi(pCre) : blo(pCre); C.y = -(m ? bhi(pCim) : blo(pCim));
                    B.x = dt * (m ? bhi(pBre) : blo(pBre)); B.y = -dt * (m ? bhi(pBim) : blo(pBim));
                    r0[m] = cmul(C, B);
                }
                const uint32_t pp = pt + lane * 8;
#define PST(j, v) sts64(pp + (j) * PT_PITCH, pack2(v[0].x, v[0].y), pack2(v[1].x, v[1].y))
#define CM(d, a, c) d[0] = cmul(a[0], c[0]); d[1] = cmul(a[1], c[1])
                PST(0, r0); CM(t, r0, z); PST(1, t); CM(r2, t, z); PST(2, r2); CM(t, r2, z); PST(3, t); CM(r4, t, z); PST(4, r4);
                CM(r2, r2, w); PST(9, r2); CM(t, r4, z); PST(5, t); CM(r2, t, z); PST(6, r2); CM(t, r2, z); PST(7, t); CM(r2, r2, w); PST(11, r2);
                CM(r0, r0, w); PST(8, r0); CM(r4, r4, w); PST(10, r4); CM(r0, r0, w); PST(12, r0); CM(r4, r4, w); PST(13, r4);
                CM(r0, r0, w); PST(14, r0); CM(r4, r4, w); PST(15, r4);
                CM(r2, w, w); CM(r4, r0, w); PST(16, r4); CM(r0, r0, r2); PST(17, r0); CM(r4, r4, r2); PST(18, r4); CM(r0, r0, r2); PST(19, r0); CM(r4, r4, r2); PST(20, r4);
#undef PST
#undef CM
            }
            {
                float ds[4] = {0.f, 0.f, 0.f, 0.f}, d0[4] = {0.f, 0.f, 0.f, 0.f}, d1[4] = {0.f, 0.f, 0.f, 0.f};
                asm volatile("cp.async.wait_all;" ::: "memory");
                __syncwarp();
                uint32_t a[4][4];
#pragma unroll
                for (int i = 0; i < 4; i++) ldsm4(a[i], sb + SM_XS + warp * 2048 + (lane & 15) * 128 + (((2 * i + (lane >> 4)) ^ (lane & 7)) << 4));
#pragma unroll
                for (int i = 0; i < 4; i++) {
                    mma(ds, a[i][0], a[i][1], a[i][2], a[i][3], 0x3F803F80u, 0x3F803F80u);
                    mma(d0, a[i][0], a[i][1], a[i][2], a[i][3], a[i][0], a[i][2]); mma(d1, a[i][0], a[i][1], a[i][2], a[i][3], a[i][1], a[i][3]);
                }
                if (q == (g >> 1)) {
                    const uint32_t a = sb + SM_RED + g * 64 + warp * 8;
                    sts64(a, fbits(ds[0]), fbits((g & 1) ? d0[1] : d0[0])); sts64(a + 512, fbits(ds[2]), fbits((g & 1) ? d1[3] : d1[2]));
                }
            }
            ep += 1;
            bar_sync(5, 384);
            const uint4 sc0 = lds128(sb + SM_SCV + q * 16), sc1 = lds128(sb + SM_SCV + 64 + q * 16);
            const uint32_t ta = sb + SM_WM + lane * 128 + ((warp ^ (lane & 7)) << 4);
            uint32_t* mq = &G.modq[3072 * (b & 7) + mcol + 8 * warp + 2 * q];
            float KA[2][3][4];
#pragma unroll
            for (int n = 0; n < 24; n++) (&KA[0][0][0])[n] = 0.f;
            const uint32_t ba = pt + (lane & 7) * PT_PITCH + (lane >> 3) * 16, pa_ = pt + 24 * PT_PITCH + q * 16;
            const float gf = (float)g;
#pragma unroll 1
            for (int k = 0; k < 2; k++) {
                uint32_t bb[2][3][4];
                uint4 pv[8];
#pragma unroll
                for (int i = 0; i < 8; i++) {
                    pv[i] = lds128(pa_ + k * 512 + i * 64);
                    if (i >= 2) ldsm4(bb[(i - 2) / 3][(i - 2) % 3], ba + ((i - 2) % 3) * 8 * PT_PITCH + k * 128 + ((i - 2) / 3) * 64);
                }
#pragma unroll
                for (int h = 0; h < 4; h++) {
                    uint32_t a[2][4];
#pragma unroll
                    for (int m = 0; m < 2; m++) {
                        const uint4 p = pv[2 * h + m];
                        cf e = cexp2(gf * __uint_as_float(p.x), gf * __uint_as_float(p.y)), z64;
                        z64.x = __uint_as_float(p.z); z64.y = __uint_as_float(p.w);
                        a[0][2 * m] = pack2(e.x, e.y); e = cmul(e, z64); a[0][2 * m + 1] = pack2(e.x, e.y); e = cmul(e, z64);
                        a[1][2 * m] = pack2(e.x, e.y); e = cmul(e, z64); a[1][2 * m + 1] = pack2(e.x, e.y);
                    }
#pragma unroll
                    for (int n = 0; n < 3; n++) { mmap(KA[0][n], a[0], bb[h >> 1][n] + 2 * (h & 1)); mmap(KA[1][n], a[1], bb[h >> 1][n] + 2 * (h & 1)); }
                }
                mbar_wait(BAR(B_WM + k)); mbar_wait(BAR(B_WM + 2 * k));
                uint32_t mb[4][4];
                ldsm4t(mb[0], ta + k * 8192); ldsm4t(mb[1], ta + k * 8192 + 4096); ldsm4t(mb[2], ta + k * 16384); ldsm4t(mb[3], ta + k * 16384 + 4096);
                float d[4][4];
#pragma unroll
                for (int i = 0; i < 4; i++) { d[i][0] = d[i][1] = d[i][2] = d[i][3] = 0.f; mma(d[i], sc0.x, sc0.y, sc0.z, sc0.w, mb[i & 2][2 * (i & 1)], mb[i & 2][2 * (i & 1) + 1]); }
#pragma unroll
                for (int i = 0; i < 4; i++) mma(d[i], sc1.x, sc1.y, sc1.z, sc1.w, mb[(i & 2) + 1][2 * (i & 1)], mb[(i & 2) + 1][2 * (i & 1) + 1]);
                const bool hi = g & 1;
                asm volatile("{.reg .pred p; .reg .b64 t; setp.lt.s32 p, %3, 2; mov.b64 t, {%1,%2}; @p st.relaxed.gpu.global.b64 [%0], t;}"
                             ::"l"(mq), "r"(tagf(hi ? d[2][0] + d[3][2] : d[0][0] + d[1][2], ep)), "r"(fbits(hi ? d[2][1] + d[3][3] : d[0][1] + d[1][3])), "r"(g) : "memory");
                mq += 512 * (b >> 6) + 1024 + 512 * (g & 1);
            }
            if (warp == 7) bulk_e(sb + SM_ST, G.stats0, 8192, BAR(B_ST));
            float (*KG)[4] = KA[0];
            const uint32_t sw = pt + lane * 16;
            __syncwarp();
#define F4(v) make_uint4(fbits(v[0]), fbits(v[1]), fbits(v[2]), fbits(v[3]))
            if (mh) {
#pragma unroll
                for (int n = 0; n < 3; n++) { sts128(sw + n * 512, F4(KA[0][n])); KG[n][0] = KA[1][n][0]; KG[n][1] = KA[1][n][1]; KG[n][2] = KA[1][n][2]; KG[n][3] = KA[1][n][3]; }
            } else {
#pragma unroll
                for (int n = 0; n < 3; n++) sts128(sw + n * 512, F4(KA[1][n]));
            }
            bar_sync(1, 256);
#pragma unroll
            for (int n = 0; n < 3; n++) {
                const uint4 v = lds128(sw + (mh ? -PT_B : PT_B) + n * 512);
                KG[n][0] += __uint_as_float(v.x); KG[n][1] += __uint_as_float(v.y); KG[n][2] += __uint_as_float(v.z); KG[n][3] += __uint_as_float(v.w);
            }
            if (mh == 0 && lane == 0) KG[0][0] += blo(dsk);
#pragma unroll
            for (int n = 0; n < 3; n++)
#pragma unroll
                for (int e = 0; e < 2; e++) {
                    const uint32_t a = sa_[n][e], v = pack2(KG[n][e], KG[n][2 + e]);
                    const bool ok0 = n < 2 || q < 2 || (e == 0 && q == 2 && mh == 0), ok1 = n < 2 || q < 2;
                    if (ok0) { sts16(a, v); sts16(a + 6, v); }
                    if (ok1) { sts16(a + 32, v >> 16); sts16(a + 38, v >> 16); }
                }
        }
        {
            const int rho = wt & 7, hh = (wt >> 3) & 1;
            mbar_wait(BAR(B_MOD));
            uint4 mo = lds128(sb + SM_OWN);
            const uint32_t tg = ep << 31;
            mo.z ^= tg | (tg >> 16); mo.w ^= tg | (tg >> 16);
            {
                const int blk = tid >> 4;
                const int t0 = 128 * blk + 32 * hh + rho - 5, e0 = t0 < 0 ? 8 : 0, e9 = t0 >= 2048 - 96 ? 88 : 96;
#define ROW(i) ((i) == 0 ? e0 : (i) == 9 ? e9 : ((i) / 5) * 64 + ((i) % 5) * 8)
                mbar_wait(BAR(B_XC));
                uint32_t st[10];
                uint2 xv[10];
#pragma unroll 1
                for (;;) {
                    mbar_wait(BAR(B_ST));
                    uint32_t bad = 0;
#pragma unroll
                    for (int i = 0; i < 10; i++) st[i] = lds32(sb + SM_ST + (t0 + ROW(i)) * 4);
#pragma unroll
                    for (int i = 0; i < 10; i++) xv[i] = lds64(sb + SM_XC + t0 * 16 + 8 * pr + 1024 * (i & 1) + 128 * (i >> 1));
#pragma unroll
                    for (int i = 0; i < 10; i++) bad = stale(bad, st[i], tg);
                    if (!RARE(any(bad >> 31))) break;
                    const int r0 = min(max(128 * (blk & ~1) - 16 + 12 * lane, 0), 2036);
                    const uint4 a = ldr128(&G.stats0[r0]), c = ldr128(&G.stats0[r0 + 4]), d = ldr128(&G.stats0[r0 + 8]);
                    sts128(sb + SM_ST + 4 * r0, a); sts128(sb + SM_ST + 4 * r0 + 16, c); sts128(sb + SM_ST + 4 * r0 + 32, d);
                    __syncwarp();
                }
#undef ROW
                const uint32_t uw = sb + SM_UW + (blk + 1) * 640 + hh * 320 + rho * 8, xb = sb + SM_XS + 4 * (160 * blk + 40 * hh + rho - 5);
                uint32_t hp[2][2];
#pragma unroll
                for (int i = 0; i < 5; i++) {
                    uint32_t h[2][2];
#pragma unroll
                    for (int u = 0; u < 2; u++) {
                        const uint2 xc = xv[2 * i + u];
                        h[u][0] = hfma2(hnorm2(xc.x, st[5 * u + i]), mo.z, mo.x); h[u][1] = hfma2(hnorm2(xc.y, st[5 * u + i]), mo.w, mo.y);
                        if ((u == 0 && i == 0 && e0) || (u == 1 && i == 4 && e9 == 88)) h[u][0] = h[u][1] = 0u;
                        const uint32_t xd = xb + 320 * u + 32 * i + (i == 4 && rho >= 5 ? 32 : 0);
                        if (i || (u == 0 && (unsigned)t0 < 3u)) { sts32(xd, xc.x); sts32(xd + XS_B, xc.y); }
                    }
#pragma unroll
                    for (int c = 0; c < 4; c++) {
                        const uint32_t sel = (c & 1) ? 0x7632u : 0x5410u;
                        if (i) sts64(uw + c * UW_B + 160 * ((i - 1) >> 1) + 64 * ((i - 1) & 1), prmt(hp[0][c >> 1], h[0][c >> 1], sel), prmt(hp[1][c >> 1], h[1][c >> 1], sel));
                        else if ((unsigned)t0 < 3u) sts32(uw + c * UW_B - 92, prmt(0u, h[0][c >> 1], sel));
                    }
                    hp[0][0] = h[0][0]; hp[0][1] = h[0][1]; hp[1][0] = h[1][0]; hp[1][1] = h[1][1];
                }
            }
        }
        RELANE()
        bar_sync(1, 256);
        {
            const int o = g - 2 * q;
            const uint32_t wd = sb + SM_WD + w4 * WD_B + 4 * o;
            const uint32_t sel0 = (o >= 0 ? 0x54u : 0x10u) | (o >= 1 ? 0x7600u : 0x3200u);
            const uint32_t oz = lds32(sb + SM_UW + 4 * lane);
            uint32_t ub = sb + SM_UW + w4 * UW_B + 160 * q + 8 * g;
            uint32_t dep = sb + SM_DEP + w4 * 512 + lane * 16;
            const float zero4[4] = {0.f, 0.f, 0.f, 0.f};
            uint32_t A[32][4], f[9][2];
#define LT(T, h) lds32(wd + 4 * ((T) + 8 * (h)))
#define QUAD(Q, a0, a1, a2, a3, id) { Q[0] = a0; Q[1] = a1; Q[2] = cpy(a2, oz, 4 * (id) + 101); Q[3] = cpy(a3, oz, 4 * (id) + 103); }
#define QF(Q, X, L, id) QUAD(Q, X[2 * (L)], X[2 * (L) + 1], (L) ? X[(L) ? 2 * (L) - 1 : 0] : 0u, X[2 * (L)], 16 * (id) + (L))
#define AN(e, L) A[3 * (e) + (L)]
#define AM(e, L) A[24 + 2 * (e) + (L) - 3]
#define A0(a) A[a]
#define A4(a) A[11 + (a)]
#define LF(k) { const uint2 v_ = lds64(ub + (8 - (k)) * 8); f[k][0] = v_.x; f[k][1] = v_.y; }
#define SUM3(d, a, c, e) { d[0] = hadd2(hadd2(f[a][0], f[c][0]), f[e][0]); d[1] = hadd2(hadd2(f[a][1], f[c][1]), f[e][1]); }
#define SUMX(d, p, a, c) { d[0] = hadd2(p[0], hadd2(f[a][0], f[c][0])); d[1] = hadd2(p[1], hadd2(f[a][1], f[c][1])); }
            if (!s) {
                {
                    const uint32_t sel1 = (o >= 1 ? 0x54u : 0x10u) | (o >= 2 ? 0x7600u : 0x3200u);
                    uint32_t T0[10], T4[10], X[10];
#pragma unroll
                    for (int h = 0; h < 10; h++) { T0[h] = LT(T0o, h); T4[h] = LT(T4o, h); }
#pragma unroll
                    for (int L = 0; L < 3; L++) { QF(AN(2, L), T0, L, 0) QF(AN(6, L), T4, L, 1) }
#pragma unroll
                    for (int L = 3; L < 5; L++) { QF(AM(1, L), T0, L, 0) QF(AM(3, L), T4, L, 1) }
#pragma unroll
                    for (int k = 0; k < 2; k++) {
#pragma unroll
                        for (int h = 0; h < 9; h++) X[h] = LT(k ? T2o : TM2o, h);
                        X[8] = prmt(X[8], T0[8], k ? sel0 : sel1); X[9] = cpy(T0[9], oz, 11 + 2 * k);
#pragma unroll
                        for (int L = 0; L < 3; L++) QF(AN(4 * k, L), X, L, 2 + k)
#pragma unroll
                        for (int L = 3; L < 5; L++) QF(AM(2 * k, L), X, L, 2 + k)
                    }
#pragma unroll
                    for (int k = 0; k < 4; k++) {
#pragma unroll
                        for (int h = 0; h < 5; h++) X[h] = LT(k == 0 ? TM1o : k == 1 ? T1o : k == 2 ? T3o : T5o, h);
                        X[4] = prmt(X[4], k < 2 ? T0[4] : T4[4], k ? sel0 : sel1); X[5] = cpy(k < 2 ? T0[5] : T4[5], oz, 19 + 2 * k);
#pragma unroll
                        for (int L = 0; L < 3; L++) QF(AN(2 * k + 1, L), X, L, 4 + k)
                    }
                }
                float Pa[5][4], Ra[3][4];
                uint32_t u3[2];
                LF(1) LF(2)
                mmar(Pa[1], zero4, AN(0, 1), f[1]); mmar(Pa[2], zero4, AN(0, 2), f[1]);
                mmar(Pa[3], zero4, AM(0, 3), f[1]); mmar(Pa[4], zero4, AM(0, 4), f[1]);
                mmar(Ra[1], zero4, AN(1, 1), f[2]); mmar(Ra[2], zero4, AN(1, 2), f[2]);
                mmap(Pa[3], AM(1, 3), f[2]); mmap(Pa[4], AM(1, 4), f[2]);
                uint32_t fb[9][2], nb = BAR(B_NEAR);
#define LOADB(F, off) _Pragma("unroll") for (int k = 1; k < 9; k++) { const uint2 v_ = lds64(ub + (off) + (8 - k) * 8); F[k][0] = v_.x; F[k][1] = v_.y; }
#define DEPOSIT(off) { sts128(dep + (off) * 2048, make_uint4(fbits(Pa[0][0] + Ra[0][0]), fbits(Pa[0][1] + Ra[0][1]), fbits(Pa[0][2] + Ra[0][2]), fbits(Pa[0][3] + Ra[0][3]))); \
                    __syncwarp(); if (lane == 0) mbar_arrive(nb + 8 * (off)); }
#define NEAR(f) { SUM3(u3, 2, 4, 3) \
                    mmar(Pa[0], Pa[1], AN(0, 0), f[1]); mmar(Pa[1], Pa[2], AN(0, 1), f[1]); mmar(Pa[2], Pa[3], AN(0, 2), f[1]); \
                    mmar(Pa[3], Pa[4], AM(0, 3), f[1]); mmar(Pa[4], zero4, AM(0, 4), f[1]); \
                    mmar(Ra[0], Ra[1], AN(1, 0), f[2]); mmar(Ra[1], Ra[2], AN(1, 1), f[2]); mmar(Ra[2], zero4, AN(1, 2), f[2]); \
                    mmap(Pa[0], AN(2, 0), f[3]); mmap(Pa[1], AN(2, 1), f[3]); mmap(Pa[2], AN(2, 2), f[3]); \
                    mmap(Pa[3], AM(1, 3), u3); mmap(Pa[4], AM(1, 4), u3); \
                    SUM3(u3, 6, 8, 7) \
                    mmap(Ra[0], AN(3, 0), f[4]); mmap(Ra[1], AN(3, 1), f[4]); mmap(Ra[2], AN(3, 2), f[4]); \
                    mmap(Pa[0], AN(4, 0), f[5]); mmap(Pa[1], AN(4, 1), f[5]); mmap(Pa[2], AN(4, 2), f[5]); \
                    mmap(Ra[0], AN(5, 0), f[6]); \
                    mmap(Pa[3], AM(2, 3), f[5]); mmap(Pa[4], AM(2, 4), f[5]); \
                    mmap(Pa[0], AN(6, 0), f[7]); mmap(Ra[1], AN(5, 1), f[6]); \
                    mmap(Ra[0], AN(7, 0), f[8]); mmap(Ra[2], AN(5, 2), f[6]); \
                    mmap(Pa[1], AN(6, 1), f[7]); mmap(Pa[2], AN(6, 2), f[7]); \
                    mmap(Pa[3], AM(3, 3), u3); mmap(Pa[4], AM(3, 4), u3); \
                    mmap(Ra[1], AN(7, 1), f[8]); mmap(Ra[2], AN(7, 2), f[8]); }
                LOADB(f, 640)
#pragma unroll 1
                for (int i = 0; i < 7; i++) {
                    LOADB(fb, 1280)
                    NEAR(f)
                    LOADB(f, 1920)
                    DEPOSIT(0)
                    { uint32_t (*f)[2] = fb; NEAR(f) }
                    DEPOSIT(1)
                    ub += 1280; dep += 4096; nb += 16;
                }
                LOADB(fb, 1280)
                mmar(Pa[0], Pa[1], AN(0, 0), f[1]); mmar(Ra[0], Ra[1], AN(1, 0), f[2]);
#pragma unroll
                for (int e = 0; e < 8; e += 2) {
                    mmap(Pa[2], AN(e, 1), f[e + 1]); mmap(Ra[2], AN(e + 1, 1), f[e + 2]);
                    if (e) { mmap(Pa[0], AN(e, 0), f[e + 1]); mmap(Ra[0], AN(e + 1, 0), f[e + 2]); mmap(Pa[4], AN(e, 0), fb[e + 1]); mmap(Pa[3], AN(e + 1, 0), fb[e + 2]); }
                    else { mmar(Pa[4], zero4, AN(0, 0), fb[1]); mmar(Pa[3], zero4, AN(1, 0), fb[2]); }
                }
#pragma unroll
                for (int i = 0; i < 4; i++) Pa[2][i] = (Pa[2][i] + Pa[4][i]) + (Ra[2][i] + Pa[3][i]);
                sts128(dep + 2048, F4(Pa[2]));
                DEPOSIT(0)
#undef LOADB
#undef DEPOSIT
#undef NEAR
            } else {
                {
                    const uint32_t selp = (g & 1) ? 0x7610u : 0x1010u;
                    uint32_t T0[33], T4[32];
#pragma unroll
                    for (int h = 9; h < 33; h++) T0[h] = LT(T0o, h);
#pragma unroll
                    for (int h = 9; h < 17; h++) T4[h] = LT(T4o, h);
                    const uint32_t T3x = prmt(T4[16], T0[16], sel0), T5x = prmt(T4[16], LT(T0o + 1, 16), sel0), T5y = LT(T0o + 1, 17);
                    QUAD(A[22], T3x, cpy(T0[17], oz, 11), T4[15], T3x, 2)
                    QUAD(A[23], q ? T5x : (T5x & 0xFFFF0000u), q ? T5y : (T5y & 0xFFFF0000u), T4[15], T5x, 3)
#pragma unroll
                    for (int h = 16; h < 32; h++) {
                        const uint32_t v = prmt(lds32(wd + 4 * (g & 1) + 4 * (T0o + 8 * h)), T0[h], selp);
                        T4[h] = h == 16 ? prmt(T4[16], v, sel0) : v;
                    }
                    QUAD(A[24], 0u, 0u, T0[31], q == 3 ? (T0[32] & 0xFFFF0000u) : 0u, 4)
#pragma unroll
                    for (int L = 5; L < 16; L++) { QF(A0(L - 5), T0, L, 0) QF(A4(L - 5), T4, L, 1) }
                }
                float Fa[12][4], Fx[4];
                uint32_t u3[2], u5[2], u7[2];
                LF(0) LF(1) LF(2)
                u5[0] = hadd2(f[1][0], f[2][0]); u5[1] = hadd2(f[1][1], f[2][1]); u7[0] = hadd2(u5[0], f[0][0]); u7[1] = hadd2(u5[1], f[0][1]);
#pragma unroll
                for (int a = 0; a < 11; a++) mmar(Fa[a], zero4, A0(a), a < 4 ? u5 : u7);
                mmar(Fa[11], zero4, A[24], u7);
                ub += 640;
                LF(0) LF(1) LF(2) LF(3) LF(4) LF(5) LF(6) LF(7) LF(8)
                uint32_t xa = sb + SM_XS + (w4 >> 1) * XS_B + 4 * (8 * g + 2 * q + 8 * (g >> 2)), nb = BAR(B_NEAR);
                bf16* xo = G.x2t + (size_t)(4 * b + w4) * 2048 + 8 * g + 2 * q;
                const uint32_t xsel = (w4 & 1) ? 0x7632u : 0x5410u;
                uint32_t ga = 0;
                const uint32_t tm = lane == 12 || lane == 29;
                sts128(dep - 2048, F4(Fa[0]));
#define FARLOOP(NA, N) _Pragma("unroll 1") for (int i = 0; i < N; i++) { \
                    const uint2 x0 = lds64(xa), x1 = lds64(xa + 320); \
                    uint4 fv = make_uint4(0, 0, 0, 0); \
                    if (NA < 11) fv = lds128(dep - 10240); \
                    if (NA) { \
                        ub += 640; \
                        SUM3(u3, 6, 8, 7) SUM3(u5, 2, 4, 3) SUMX(u5, u5, 1, 5) \
                        if (NA > 3) { SUMX(u7, u5, 0, 6) LF(0) } \
                        LF(1) LF(2) LF(3) LF(4) LF(5) \
                        mmar(Fa[0], Fa[1], A4(0), u3); mmar(Fa[1], Fa[2], A4(1), u3); mmar(Fa[2], Fa[3], A4(2), u3); \
                        if (NA > 3) { \
                            mmar(Fa[3], Fa[4], A[22], f[6]); mmar(Fx, zero4, A[23], f[8]); \
                            _Pragma("unroll") for (int a = 4; a < NA; a++) mmar(Fa[a], Fa[a + 1], A4(a), f[7]); \
                            mmap(Fa[3], A4(3), f[7]); mmap(Fx, A0(3), u5); \
                        } \
                        LF(6) LF(7) LF(8) \
                        mmap(Fa[0], A0(0), u5); mmap(Fa[1], A0(1), u5); mmap(Fa[2], A0(2), u5); \
                        if (NA > 3) { \
                            _Pragma("unroll") for (int a = 4; a < NA; a++) mmap(Fa[a], A0(a), u7); \
                            Fa[3][0] += Fx[0]; Fa[3][1] += Fx[1]; Fa[3][2] += Fx[2]; Fa[3][3] += Fx[3]; \
                        } \
                    } \
                    if (NA == 11 && i == 0) { mbar_wait(BAR(B_MOD + 1)); ga = lds32(sb + SM_OWN + 16 + 4 * (w4 >> 1)); ga = prmt(ga, ga, xsel); } \
                    mbar_wait(nb); \
                    const uint4 nv = lds128(dep); \
                    if (NA) sts128(dep, F4(Fa[0])); \
                    float y[4] = {__uint_as_float(nv.x), __uint_as_float(nv.y), __uint_as_float(nv.z), __uint_as_float(nv.w)}; \
                    if (NA < 11) { y[0] += __uint_as_float(fv.x); y[1] += __uint_as_float(fv.y); y[2] += __uint_as_float(fv.z); y[3] += __uint_as_float(fv.w); } \
                    stg32(xo, tagm(hfma2(ga, pack2(y[0], y[1]), prmt(x0.x, x0.y, xsel)), ep, tm)); \
                    stg32(xo + 64, tagm(hfma2(ga, pack2(y[2], y[3]), prmt(x1.x, x1.y, xsel)), ep, tm)); \
                    if (NA == 3 && i == 0) { red_add_e(&G.cnt[(b >> 4) * 32]); if (lane == 0) mbar_arrive(BAR(B_CONV)); } \
                    xa += 640; xo += 128; dep += 2048; nb += 8; }
                FARLOOP(11, 4) FARLOOP(7, 4)
                FARLOOP(3, 3)
                FARLOOP(0, 3)
                {
                    uint2 x0[2], x1[2]; uint4 fv[2], nv[2];
#pragma unroll
                    for (int i = 0; i < 2; i++) { x0[i] = lds64(xa + 640 * i); x1[i] = lds64(xa + 640 * i + 320); fv[i] = lds128(dep + 2048 * i - 10240); }
                    mbar_wait(nb);
                    nv[0] = lds128(dep); nv[1] = lds128(dep + 2048);
#pragma unroll
                    for (int i = 0; i < 2; i++) {
                        stg32(xo + 128 * i, tagm(hfma2(ga, pack2(__uint_as_float(nv[i].x) + __uint_as_float(fv[i].x), __uint_as_float(nv[i].y) + __uint_as_float(fv[i].y)), prmt(x0[i].x, x0[i].y, xsel)), ep, tm));
                        stg32(xo + 128 * i + 64, tagm(hfma2(ga, pack2(__uint_as_float(nv[i].z) + __uint_as_float(fv[i].z), __uint_as_float(nv[i].w) + __uint_as_float(fv[i].w)), prmt(x1[i].x, x1[i].y, xsel)), ep, tm));
                    }
                }
                red_add_e(&G.cnt[(8 + (b >> 4)) * 32]);
                if (lane == 0) mbar_arrive(BAR(B_CONV + 1));
#undef FARLOOP
                {
                    const uint32_t va = g < 2 ? sb + SM_CBV + 1024 * g + 128 * w4 + 16 * q : sb + SM_ONE, vs = g < 2 ? 64 : 0, vp = 8 * vs;
                    mbar_wait(BAR(B_W1RDY)); mbar_wait(BAR(B_W1C));
                    const uint4 v[4] = {lds128(va + pr * vp), lds128(va + pr * vp + vs), lds128(va + (pr ^ 1) * vp), lds128(va + (pr ^ 1) * vp + vs)};
                    uint32_t bb[2][4];
                    ldsm4t(bb[0], sb + SM_W1C + w4 * 1024 + lane * 16); ldsm4t(bb[1], sb + SM_W1C + w4 * 1024 + 512 + lane * 16);
                    float d[4][4];
#pragma unroll
                    for (int i = 0; i < 16; i++) (&d[0][0])[i] = 0.f;
#pragma unroll
                    for (int i = 0; i < 4; i++) {
                        mma(d[0], v[i].x, v[i].y, v[i].z, v[i].w, v[i].x, v[i].z); mma(d[1], v[i].x, v[i].y, v[i].z, v[i].w, v[i].y, v[i].w);
                        if (i < 2) { mma(d[2], v[i].x, v[i].y, v[i].z, v[i].w, bb[i][0], bb[i][1]); mma(d[3], v[i].x, v[i].y, v[i].z, v[i].w, bb[i][2], bb[i][3]); }
                    }
                    const uint32_t ra = sb + SM_ARED + 32 * lane + 8 * w4;
                    if (g < 4) { sts64(ra, fbits(d[0][0] + d[1][2]), fbits(d[0][1] + d[1][3])); sts64(ra + 512, fbits(d[2][0] + d[3][2]), fbits(d[2][1] + d[3][3])); }
                    warp_arrive(BAR(B_AUXQ));
                }
            }
#undef LT
#undef QUAD
#undef QF
#undef LF
#undef SUM3
#undef SUMX
#undef AN
#undef AM
#undef A0
#undef A4
        }

        RELANE()
        const int tau = 16 * s + gi, row0 = 64 * tau + 16 * w4 + g;
        float acc[32];
        {
#define VCOORD const int vrow = 16 * w4 + (lane & 15), vcol = 32 * (lane >> 4); \
            const uint32_t vo = sb + vrow * 128 + (((4 * (lane >> 4) + 3) ^ (lane & 7)) << 4) + 4 * (lane >> 4);
            VCOORD
            uint32_t W[128], x2p[16], xT[16];
            const uint32_t xt = s ? SM_P1 : SM_Q, stg = sb + SM_Q + (8 + s) * 8192, tb = sb + SM_TB + s * 1792;
            const uint32_t tofs = (8 * (lane >> 4) + (lane & 7)) * 128 + (((2 * w4 + ((lane >> 3) & 1)) ^ (lane & 7)) << 4);
            const uint32_t nofs = vrow * 128 + (((lane >> 4) ^ (lane & 7)) << 4);
            const bf16* xsrc = G.x2t + (size_t)vrow * 2048 + 64 * tau + vcol;
#define LOADW(j, p) _Pragma("unroll") for (int k = 0; k < 8; k++) ldsm4t(W + 32 * (j) + 4 * k, sb + SM_W1 + (p) * 16384 + tofs + k * 2048);
#define PAIR(j, TB, db, step, first) { WG_FENCE(); \
            _Pragma("unroll") for (int k = 0; k < 8; k++) { const uint32_t* a = W + 32 * (j) + 4 * k; wgmma_rs64<TB>(acc, a[0], a[1], a[2], a[3], (db) + step, !(first) || k != 0); } \
            WG_COMMIT(); }
            const uint32_t rofs = stg + w4 * 2048 + (lane >> 3) * 128 + (((lane ^ (lane >> 3)) & 7) << 4);
            const uint32_t gofs = (64 * tau + 16 * w4 + (lane >> 3)) * 512 + 64 * cs + 8 * (lane & 7);
#define STORE(o, dst, hint) { _Pragma("unroll") for (int n = 0; n < 4; n++) stsm4t(stg + tofs + n * 2048, o[4 * n], o[4 * n + 1], o[4 * n + 2], o[4 * n + 3]); \
            bar_sync(2 + s, 128); store_rows<true>(rofs, dst + gofs, lane, ep); red_add_e(hint); }
            const int p0 = cs >> 1;
            mbar_wait(BAR(s ? B_WA : B_W1FULL));
            LOADW(0, p0) LOADW(1, (p0 + 1) & 3) LOADW(2, (p0 + 2) & 3) LOADW(3, (p0 + 3) & 3)
            fence_async_smem();
            warp_arrive(BAR(s ? B_WA + 1 : B_WA));
            mbar_wait(BAR(B_W1RDY));
            {
                const uint32_t ca_ = sb + SM_CBV + 128 * cs + 16 * q, va = g < 2 ? ca_ + 1024 * g : sb + SM_ONE;
                const uint4 c0 = lds128(ca_), c1_ = lds128(ca_ + 64), v0 = lds128(va), v1 = lds128(va + (g < 2 ? 64 : 0));
                const uint32_t cw[8] = {c0.x, c0.z, c0.y, c0.w, c1_.x, c1_.z, c1_.y, c1_.w}, vw[8] = {v0.x, v0.z, v0.y, v0.w, v1.x, v1.z, v1.y, v1.w};
                uint2 rec[2];
#pragma unroll 1
                for (;;) {
                    mbar_wait(BAR(B_PAIR + 4 * s + (cs >> 1)));
#pragma unroll
                    for (int n = 0; n < 4; n++) ldsm4t(x2p + 4 * n, sb + xt + cs * 8192 + tofs + n * 2048);
                    const uint32_t tg = lds32(vo + xt + cs * 8192);
                    float d[6][4];
#pragma unroll
                    for (int i = 0; i < 24; i++) (&d[0][0])[i] = 0.f;
#pragma unroll
                    for (int k = 0; k < 4; k++) {
                        const uint32_t* x = x2p + 4 * k;
                        const uint32_t y[4] = {hmul2(x[0], cw[2 * k]), hmul2(x[1], cw[2 * k]), hmul2(x[2], cw[2 * k + 1]), hmul2(x[3], cw[2 * k + 1])};
                        mma(d[0], x[0], x[1], x[2], x[3], 0x3F803F80u, 0x3F803F80u); mma(d[2], x[0], x[1], x[2], x[3], x[0], x[2]); mma(d[3], x[0], x[1], x[2], x[3], x[1], x[3]);
                        mma(d[1], y[0], y[1], y[2], y[3], vw[2 * k], vw[2 * k + 1]); mma(d[4], y[0], y[1], y[2], y[3], y[0], y[2]); mma(d[5], y[0], y[1], y[2], y[3], y[1], y[3]);
                    }
                    const int dl = (lane & 28) + (g >> 1);
#pragma unroll
                    for (int r = 0; r < 2; r++) {
                        const float xx = __shfl_sync(0xffffffffu, (g & 1) ? d[2 + r][2 * r + 1] : d[2 + r][2 * r], dl);
                        const float yy = __shfl_sync(0xffffffffu, (g & 1) ? d[4 + r][2 * r + 1] : d[4 + r][2 * r], dl);
                        rec[r].x = tagf(q < 2 ? d[1][2 * r] : xx, ep); rec[r].y = fbits(q == 0 ? d[1][2 * r + 1] : q == 1 ? d[0][2 * r] : yy);
                    }
                    if (!RARE(bar_any(2 + s, 128, tg ^ ep))) break;
                    refetch<1, 0, false>(vo + xt + cs * 8192, ep, xsrc + (size_t)cs * 64 * 2048);
                    bar_sync(2 + s, 128);
                }
                uint2* sd = (uint2*)(G.stats1 + ((tau * 8 + cs) * 64 + 16 * w4 + g) * 2) + q;
                str64(sd, rec[0].x, rec[0].y); str64(sd + 32, rec[1].x, rec[1].y);
            }
            const uint4* sp = G.stats1 + tau * 1024 + wt;
            uint4 pm[8];
#pragma unroll 1
            for (;;) {
#define CPAIR(j) { const int p = ((j) + p0) & 3; const uint64_t db = desc(sb + xt + p * 16384, 8192); if (j) mbar_wait(BAR(B_PAIR + 4 * s + p)); PAIR(j, 1, db, 128 * k, (j) == 0) }
                CPAIR(0) CPAIR(1) CPAIR(2)
#pragma unroll
                for (int i = 0; i < 8; i++) pm[i] = ldr128(sp + 128 * i);
                CPAIR(3)
#undef CPAIR
                if (!RARE(bar_any(2 + s, 128, check_tile(vo + xt, ep)))) break;
                WG_WAIT(0);
                refetch<8, 64 * 2048, false>(vo + xt, ep, xsrc);
                bar_sync(2 + s, 128);
            }
            mbar_wait(BAR(B_CONV + 1)); mbar_wait(BAR(B_CONST));
            const uint4 k0 = lds128(sb + SM_CONST), k1 = lds128(sb + SM_CONST + 32);
            for (;;) {
                uint32_t bad = 0;
#pragma unroll
                for (int i = 0; i < 8; i += 2) bad = check(bad, make_uint4(pm[i].x, pm[i].z, pm[i + 1].x, pm[i + 1].z), ep);
                if (!RARE(any(bad))) break;
#pragma unroll
                for (int i = 0; i < 8; i++) pm[i] = ldr128(sp + 128 * i);
            }
            {
#define SUM8(f) (((__uint_as_float(pm[0].f) + __uint_as_float(pm[1].f)) + (__uint_as_float(pm[2].f) + __uint_as_float(pm[3].f))) + \
                 ((__uint_as_float(pm[4].f) + __uint_as_float(pm[5].f)) + (__uint_as_float(pm[6].f) + __uint_as_float(pm[7].f))))
                float S[6] = {SUM8(x), SUM8(y), SUM8(z), SUM8(w), 0.f, 0.f};
#undef SUM8
                S[4] = shx(S[0], 1); S[5] = shx(S[1], 1);
                const float Ccc = __uint_as_float(k0.x), Ccs = __uint_as_float(k0.y), Cc = __uint_as_float(k0.z), Css = __uint_as_float(k1.y), Cs = __uint_as_float(k1.z);
                const float n1 = 1.f / 512.f;
                const float m1 = S[3] * n1, v1 = fmaxf(fmaf(-m1, m1, S[4] * n1), 0.f) + LN_EPS, r1 = rsq(v1), sd = v1 * r1;
                const float m2 = fmaf(r1, fmaf(-m1, Cc, S[2]), Cs) * n1;
                const float e2 = fmaf(r1, fmaf(r1, fmaf(m1, fmaf(m1, Ccc, -2.f * S[0]), S[5]), 2.f * fmaf(-m1, Ccs, S[1])), Css) * n1;
                const float r2 = rsq(fmaxf(fmaf(-m2, m2, e2), 0.f) + LN_EPS);
                const int r = wt >> 1;
                if (!(lane & 1)) {
                    sts128(tb + 16 * r, make_uint4(split2(-m1), split2(sd), split2(-m2 * sd), 0u));
                    sts32(tb + 1024 + 4 * r, fbits(0.5f * r1 * r2)); sts64(tb + 1280 + 8 * r, fbits(r1), fbits(-m1 * r1));
                }
            }
            mbar_wait(BAR(B_U123));
            uint32_t u0 = lds32(sb + SM_U123 + 256 * q + 64 * w4 + 4 * g), u1 = lds32(sb + SM_U123 + 256 * q + 64 * w4 + 4 * g + 32);
            bar_sync(2 + s, 128);
            WG_WAIT(0);
            pin<32>(acc);
            {
                if (q == 3) u0 = u1 = 0;
                const uint32_t a0 = prmt(u0, u0, 0x3232u), a1 = prmt(u1, u1, 0x3232u), a2 = prmt(u0, u0, 0x1010u), a3 = prmt(u1, u1, 0x1010u);
                uint32_t cb[8], gp[16];
                float2 ah[8];
#pragma unroll
                for (int n = 0; n < 8; n++) { cb[n] = lds32(tb + 128 * n + 4 * lane); ah[n] = ldsf2(tb + 1024 + 32 * n + 8 * q); }
#pragma unroll
                for (int n = 0; n < 8; n++) mma(acc + 4 * n, a0, a1, a2, a3, cb[n], cb[n]);
#pragma unroll
                for (int i = 0; i < 16; i++) {
                    const float h0 = ah[i >> 1].x * acc[2 * i], h1 = ah[i >> 1].y * acc[2 * i + 1];
                    gp[i] = pack2(fmaf(h0, gelu_t(h0, 2.f * GK0, 8.f * GK1), h0), fmaf(h1, gelu_t(h1, 2.f * GK0, 8.f * GK1), h1));
                }
                STORE(gp, G.g + 1024, &G.flag[(tau * 8 + cs) * 32])
            }
#pragma unroll
            for (int n = 0; n < 4; n++) { ldsm4t(x2p + 4 * n, sb + xt + cs * 8192 + tofs + n * 2048); ldsm4(xT + 4 * n, sb + xt + cs * 8192 + (nofs ^ (32 * n))); }
            if ((lane == 0) | ((x2p[0] & x2p[4] & x2p[8] & x2p[12] & xT[0] & xT[4] & xT[8] & xT[12]) == 0xFFFFFFFFu)) mbar_arrive(BAR(B_TILE + s));
            mbar_wait(BAR(B_W2FULL)); LOADW(0, 0) mbar_wait(BAR(B_W2FULL + 1)); LOADW(1, 1)
            mbar_wait(BAR(B_W2FULL + 2)); LOADW(2, 2) mbar_wait(BAR(B_W2FULL + 3)); LOADW(3, 3)
            fence_async_smem();
            warp_arrive(BAR(B_WFREE));
#pragma unroll 1
            for (;;) {
                {
                    pinu<16>(xT);
                    const uint32_t a = sb + SM_CBV + vecpos(32 * cs + 8 * w4 + (g >> 1)), sel = (g & 1) ? 0x3244u : 0x1044u;
                    const float cv[2] = {__uint_as_float(prmt(lds32(a), 0, sel)), __uint_as_float(prmt(lds32(a + 8), 0, sel))};
                    const float sv[2] = {__uint_as_float(prmt(lds32(a + 1024), 0, sel)), __uint_as_float(prmt(lds32(a + 1032), 0, sel))};
#pragma unroll
                    for (int n = 0; n < 8; n++) {
                        const uint4 rc = lds128(tb + 1280 + 64 * n + 16 * q);
#pragma unroll
                        for (int r = 0; r < 2; r++) {
                            acc[4 * n + 2 * r] = fmaf(fmaf(blo(xT[2 * n + r]), __uint_as_float(rc.x), __uint_as_float(rc.y)), cv[r], sv[r]);
                            acc[4 * n + 2 * r + 1] = fmaf(fmaf(bhi(xT[2 * n + r]), __uint_as_float(rc.z), __uint_as_float(rc.w)), cv[r], sv[r]);
                        }
                    }
                }
                const uint64_t db = desc(sb + xt, 16);
#define DPAIR(j) { mbar_wait(BAR(B_PAIR + 8 + 4 * s + (j))); PAIR(j, 0, db, 1024 * (j) + 2 * (k & 3) + 512 * (k >> 2), false) }
                DPAIR(0)
                DPAIR(1) DPAIR(2) DPAIR(3)
#undef DPAIR
                const bool redo = bar_any(2 + s, 128, check_tile(vo + xt, ep));
                WG_WAIT(0);
                if (!RARE(redo)) break;
                refetch<8, 64, true>(vo + xt, ep, G.g + (size_t)(64 * tau + vrow + 2) * 512 + vcol);
                bar_sync(2 + s, 128);
            }
            pin<32>(acc);
            if (lane == 0) mbar_arrive(BAR(B_TILE + 2 + s));
#pragma unroll
            for (int i = 0; i < 16; i++) xT[i] = pack2(acc[2 * i], acc[2 * i + 1]);
            STORE(xT, G.x1, &G.flag[((32 + tau) * 8 + cs) * 32])
#pragma unroll
            for (int n = 0; n < 4; n++) ldsm4(xT + 4 * n, stg + (nofs ^ (32 * n)));
            float sm[2] = {0.f, 0.f}, sq[2] = {0.f, 0.f};
#pragma unroll
            for (int i = 0; i < 16; i++) {
                const float2 gv = ldsf2(sb + SM_GB + (8 * (i >> 1) + 2 * q) * 4);
                const float a = blo(xT[i]), c = bhi(xT[i]);
                sm[i & 1] += a + c; sq[i & 1] = fmaf(a, a, fmaf(c, c, sq[i & 1]));
                acc[2 * i] = fmaf(gv.x, a, blo(x2p[i])); acc[2 * i + 1] = fmaf(gv.y, c, bhi(x2p[i]));
            }
#pragma unroll
            for (int r = 0; r < 2; r++) { sm[r] += shx(sm[r], 1); sq[r] += shx(sq[r], 1); sm[r] += shx(sm[r], 2); sq[r] += shx(sq[r], 2); }
            if (q < 2) str64(&G.stats2[2048 * cs + row0 + 8 * q], tagf(q ? sm[1] : sm[0], ep), fbits(q ? sq[1] : sq[0]));
            warp_arrive(BAR(B_DST));
#undef LOADW
#undef PAIR
#undef STORE
        }
        RELANE()
        uint32_t H[56];
        float hr[2], X[32], Y[32];
        const uint32_t hw = sb + SM_H + (s ? 0 : 28672) + w4 * 7168, hbuf = hw + lane * 16, rb0 = mapa(bar0, pr ^ 1);
        {
            float e[112];
            VCOORD
            const uint32_t ka = sb + SM_RED + s * 1024 + (16 * w4 + g) * 16;
            const uint64_t dw = desc(sb, 8192);
            int slot = s ? 7 : 10;
#define XCHECK(c) if (RARE(any(tg ^ ep))) refetch<1, 0, false>(vo + SM_Q + slot * 8192, ep, G.x1 + (size_t)(64 * tau + vrow) * 512 + 64 * (c) + vcol);
            mbar_wait(BAR(B_X1 + 8 * s));
            uint32_t tg = lds32(vo + SM_Q + slot * 8192);
#pragma unroll 1
            for (int c = 0; c < 8; c++) {
                const uint64_t da = desc(sb + SM_Q + slot * 8192, 16), db = desc(sb + wstage(c), 4096, 0x80000020u);
                const int cn = min(c + 1, 7);
                mbar_wait(BAR(B_WFULL + c));
                XCHECK(c)
                WG_FENCE();
                wgmma_ss224(e, da, db, c != 0);
                WG_COMMIT();
                WG_WAIT(1);
                if (lane == 0 && c) mbar_arrive(BAR(B_WEMPTY + c - 1));
                if (lane == 0 && (s ? c == 4 : (unsigned)(c - 1) < 5u)) mbar_arrive_remote(s ? rb0 + 8 * B_HFREE : BAR(B_EMPTY + c - 1));
                wgmma_ss224(e, da + 2, db + 64, 1);
                if (c < 7) slot = slot == NSLOT - 1 ? 0 : slot + 1;
                wgmma_ss224(e, da + 4, db + 128, 1);
                wgmma_ss224(e, da + 6, db + 192, 1);
                WG_COMMIT();
                mbar_wait(BAR(B_X1 + 8 * s + cn));
                tg = lds32(vo + SM_Q + slot * 8192);
            }
#undef XCHECK
            mbar_wait(BAR(B_LN3 + s)); mbar_wait(BAR(B_U4));
            const uint4 c0 = lds128(ka), c1 = lds128(ka + 128);
            const float k0[2] = {__uint_as_float(c0.y), __uint_as_float(c1.y)}, k1[2] = {__uint_as_float(c0.x), __uint_as_float(c1.x)};
            hr[0] = __uint_as_float(c0.z); hr[1] = __uint_as_float(c1.z);
            WG_FENCE();
            wgmma_rs224(e, q < 2 ? c0.w : 0u, q < 2 ? c1.w : 0u, 0u, 0u, desc(sb + SM_U4, 0, 8), 1);
            WG_COMMIT();
            WG_WAIT(0);
            pin<112>(e);
            if (lane == 0) { mbar_arrive(BAR(B_WEMPTY + 7)); if (!s) mbar_arrive_remote(rb0 + 8 * (B_HFREE + 1)); }
#define SENDH(j) asm volatile("st.async.weak.shared::cluster.mbarrier::complete_tx::bytes.v4.b32 [%0], {%1,%2,%3,%4}, [%5];" \
            ::"r"(hbuf + (rb0 - bar0) + (j) * 512), "r"(H[4 * (j)]), "r"(H[4 * (j) + 1]), "r"(H[4 * (j) + 2]), "r"(H[4 * (j) + 3]), "r"(rb0 + 8 * (B_HFULL + s)) : "memory")
#define GELU(k, k1) { \
                _Pragma("unroll") for (int i = 0; i < 4; i++) { \
                    const float v0 = e[8 * (k) + 2 * i], v1 = e[8 * (k) + 2 * i + 1]; \
                    H[4 * (k) + i] = pack2(fmaf(v0, gelu_t(v0, k0[i & 1], k1[i & 1]), v0), fmaf(v1, gelu_t(v1, k0[i & 1], k1[i & 1]), v1)); \
                } }
            float ka_[2], kb_[2];
#define RL(d) { d[0] = __uint_as_float(lds32(ka)); d[1] = __uint_as_float(lds32(ka + 128)); }
#define KS(D, j, k) wgmma_rs64<1>(D, H[4 * (k)], H[4 * (k) + 1], H[4 * (k) + 2], H[4 * (k) + 3], dw + (wstage(j) >> 4) + 128 * (k), (k) != 0);
#define SEG(k, kc, kn) GELU(k, kc) GELU(k + 1, kc) if (!(k)) { mbar_wait(BAR(B_HFREE + s)); mbar_wait(BAR(B_WFULL + 8)); } \
            SENDH(k); SENDH(k + 1); RL(kn) WG_FENCE(); KS(X, 0, k) KS(X, 0, k + 1)
            RL(ka_)
            SEG(0, k1, kb_) SEG(2, ka_, ka_) SEG(4, kb_, kb_) SEG(6, ka_, ka_) SEG(8, kb_, kb_) SEG(10, ka_, ka_) SEG(12, kb_, kb_)
            WG_COMMIT();
            mbar_wait(BAR(B_WFULL + 9));
            WG_FENCE();
#pragma unroll
            for (int k = 0; k < 14; k++) KS(Y, 1, k)
            WG_COMMIT();
            WG_WAIT(1);
            warp_arrive(BAR(B_WEMPTY + 8));
#undef RL
#undef KS
#undef SEG
#undef GELU
        }
        {
            uint32_t Hp[56];
            uint4* pdst = G.part + (size_t)((gi * 8 + 4 * pr) * 6 + s) * 512 + wt;
#define TILE(D, A, j, first) { const uint64_t dt = desc(sb + wstage(j), 16 * (j));        mbar_wait(BAR(B_WFULL + 8 + (j))); WG_FENCE(); \
            _Pragma("unroll") for (int k = 0; k < 14; k++) wgmma_rs64<1>(D, A[4 * k], A[4 * k + 1], A[4 * k + 2], A[4 * k + 3], dt + 128 * k, !(first) || k != 0); \
            WG_COMMIT(); if ((j) && (j) != 5) WG_WAIT(1); if ((j) && (j) < 5) warp_arrive(BAR(B_WEMPTY + 7 + (j))); }
#define SEND(D, st_) { pin<32>(D); uint4* pd = pdst + (((pa + (st_)) & 3) * 6 + 2 * ((st_) - 1)) * 512; \
            _Pragma("unroll") for (int v = 0; v < 4; v++) str128(pd + 128 * v, make_uint4(tagw(pack2(D[8 * v], D[8 * v + 1]), ep), pack2(D[8 * v + 2], D[8 * v + 3]), \
                                                                 pack2(D[8 * v + 4], D[8 * v + 5]), pack2(D[8 * v + 6], D[8 * v + 7]))); }
            mbar_wait(BAR(B_HFULL + s));
            asm volatile("fence.acquire.sync_restrict::shared::cluster.cluster;" ::: "memory");
#pragma unroll
            for (int k = 0; k < 14; k++) {
                const uint4 v = lds128(hbuf + k * 512); Hp[4 * k] = v.x; Hp[4 * k + 1] = v.y; Hp[4 * k + 2] = v.z; Hp[4 * k + 3] = v.w;
                if (k < 8) sts128(hbuf + k * 512, make_uint4(__float_as_uint(acc[4 * k]), __float_as_uint(acc[4 * k + 1]), __float_as_uint(acc[4 * k + 2]), __float_as_uint(acc[4 * k + 3])));
            }
            pinu<56>(Hp);
            TILE(X, Hp, 2, false)
            TILE(Y, Hp, 3, false)
            SEND(X, 1)
            TILE(X, H, 4, true)
            SEND(Y, 2)
            TILE(X, Hp, 5, false)
            TILE(Y, H, 6, true)
            SEND(X, 3)
            const uint4* psrc = pdst + pa * 6 * 512;
            uint4 pv[12];

#pragma unroll
            for (int i = 0; i < 8; i++) pv[i] = ldr128(psrc + (i >> 2) * 1024 + (i & 3) * 128);
            TILE(Y, Hp, 7, false)
#pragma unroll
            for (int i = 8; i < 12; i++) pv[i] = ldr128(psrc + (i >> 2) * 1024 + (i & 3) * 128);
#pragma unroll
            for (int n = 0; n < 8; n++) {
                const float2 gv = ldsf2(sb + SM_GB + (8 * n + 2 * q) * 4);
                const uint4 t = lds128(hbuf + n * 512);
                acc[4 * n] = __uint_as_float(t.x); acc[4 * n + 1] = __uint_as_float(t.y); acc[4 * n + 2] = __uint_as_float(t.z); acc[4 * n + 3] = __uint_as_float(t.w);
                X[4 * n] = gv.x * hr[0]; X[4 * n + 1] = gv.y * hr[0]; X[4 * n + 2] = gv.x * hr[1]; X[4 * n + 3] = gv.y * hr[1];
            }
            for (;;) {
                uint32_t bad = 0;
#pragma unroll
                for (int i = 0; i < 12; i++) bad = stale(bad, pv[i].x, ep);
                if (!RARE(any(bad))) break;
#pragma unroll
                for (int i = 0; i < 12; i++) pv[i] = ldr128(psrc + (i >> 2) * 1024 + (i & 3) * 128);
            }
#pragma unroll
            for (int v = 0; v < 4; v++) {
                const uint32_t t[4] = {hadd2(hadd2(pv[v].x, pv[4 + v].x), pv[8 + v].x), hadd2(hadd2(pv[v].y, pv[4 + v].y), pv[8 + v].y),
                                       hadd2(hadd2(pv[v].z, pv[4 + v].z), pv[8 + v].z), hadd2(hadd2(pv[v].w, pv[4 + v].w), pv[8 + v].w)};
#pragma unroll
                for (int i = 0; i < 4; i++) {
                    const int j = 8 * v + 2 * i;
                    acc[j] = fmaf(X[j], blo(t[i]), acc[j]); acc[j + 1] = fmaf(X[j + 1], bhi(t[i]), acc[j + 1]);
                }
            }
            WG_WAIT(0);
            pin<32>(Y);
            uint32_t o[16];
#pragma unroll
            for (int i = 0; i < 16; i++) o[i] = pack2(fmaf(X[2 * i], Y[2 * i], acc[2 * i]), fmaf(X[2 * i + 1], Y[2 * i + 1], acc[2 * i + 1]));
#pragma unroll
            for (int n = 0; n < 4; n++) stsm4(hw + 4096 + (lane & 15) * 128 + (((2 * n + (lane >> 4)) ^ (lane & 7)) << 4), o[4 * n], o[4 * n + 1], o[4 * n + 2], o[4 * n + 3]);
            __syncwarp();
            store_rows<false>(hw + 4096 + (lane >> 3) * 128 + (((lane ^ (lane >> 3)) & 7) << 4), P.out + (uint32_t)((64 * tau + 16 * w4 + (lane >> 3)) * 512 + 64 * cs + 8 * (lane & 7)), lane, ep);
            if (tid == 128) str32(&G.epoch[b], ep);
            warp_arrive(BAR(B_DONE));
#undef TILE
#undef SEND
#undef SENDH
#undef VCOORD
        }
    } else {
        const int aw = warp - 8;
        if (aw == 0) {
            if (lane == 0) {
#pragma unroll
                for (int i = 0; i < B_EARLY; i++) mbar_init(BAR(i), 1);
            }
            __syncwarp();
            if (lane < B_MOD) mbar_expect(BAR(lane), lane == B_XC ? 32768 : 8192);
            asm volatile("fence.mbarrier_init.release.cluster;" ::: "memory");
        }
        asm volatile("barrier.cluster.arrive.relaxed.aligned;" ::: "memory");
        asm volatile("setmaxnreg.dec.sync.aligned.u32 56;");
        if (aw == 1 || aw == 2) {
            const uint32_t b0 = BAR(B_EARLY + 56 * (aw - 1));
            if (lane == 0) {
#pragma unroll
                for (int i = 0; i < 56; i++) mbar_init(b0 + 8 * i, aw == 1 || i < 7 ? 1 : i < 40 ? 4 : 8);
                asm volatile("fence.mbarrier_init.release.cluster;" ::: "memory");
            }
            __syncwarp();
            if (aw == 1) {
                mbar_expect(b0 + 8 * lane, lane < 20 ? 16384 : lane == 20 ? 4096 : lane == 21 ? 65536 : 28672);
                if (lane < 24) mbar_expect(b0 + 256 + 8 * lane, lane < 8 ? 28672 : 8192);
            }
        }
        if (!(aw & 1)) asm volatile("bar.arrive 5, 384;" ::: "memory");
        const uint32_t cw = ldg32(P.c + 64 * (b & 7) + 2 * lane);
        const uint32_t ep = ldr32(&G.epoch[b]) + 1;
        asm volatile("barrier.cluster.wait.aligned;" ::: "memory");
        RELANE()
#define at wt
        if (aw == 0) {
#pragma unroll 1
            for (int i = any(ep == 0); i < 4; i++) {
                if (i < 3) tma2d_e(sb + SM_WM + 8192 * i, &M.m[tmWm], mcol + (i ? 512 * (b >> 6) + 512 + 512 * i : 0), 64 * (b & 7), BAR(B_WM + i));
                tma2d_pair_e(sb + SM_XC + (2 * i + pr) * 4096, &M.m[tmXc], 8 * (b >> 1), 256 * (2 * i + pr), BAR(B_XC));
            }
            mbar_wait(BAR(B_ST)); mbar_wait(BAR(B_MOD));
            l2_prefetch_e(P.w3 + (size_t)b * 7168, 14336); l2_prefetch_e(P.w2 + (size_t)b * 2048, 4096); l2_prefetch_e(P.w4 + (size_t)b * 7168, 14336);
        } else if (aw == 1) {
            const uint32_t e = (ep + 1) & 1;
            const uint4 e4 = make_uint4(e | (e << 31), e | (e << 31), e | (e << 31), e | (e << 31));
            str128(&G.modq[3072 * (b & 7) + mcol + (lane >> 4) * (512 * (b >> 6) + 1024) + 4 * (lane & 15)], e4);
            if (lane < 28) str128(lane < 16 ? (void*)&G.modq[3072 * (b & 7) + mcol + 512 * (b >> 6) + 1536 + 4 * lane]
                                : lane < 20 ? (void*)&G.stats0[16 * b + 4 * (lane - 16)] : lane < 22 ? (void*)&G.modp[2 * b + lane - 20]
                                : (void*)&G.u123[1536 * pr + 512 * ((lane - 22) >> 1) + 8 * (b >> 1) + 4 * (lane & 1)], e4);
            if (lane < 16 && (gi == 0 || gi == 15)) {
                const uint32_t t = ep & 1;
                stg128(G.g + (size_t)((gi ? 2050 : 0) + (lane >> 3)) * 512 + 64 * cs + 8 * (lane & 7), t, t, t, t);
            }
            asm volatile("bar.arrive 5, 384;" ::: "memory");
        } else if (aw == 2) {
#pragma unroll 1
            for (int i = 0; i < tmCount; i++) asm volatile(ELECT "prefetch.tensormap [%0];}" ::"l"(&M.m[i]) : "memory");
            mbar_wait(BAR(B_WM + 2));
            uint4 w[8];
#pragma unroll
            for (int i = 0; i < 8; i++) w[i] = ldg128(P.w1 + (size_t)b * 2048 + 256 * i + 8 * lane);
            mbar_wait(BAR(B_MOD + 1));
            const uint2 cc = lds64(sb + SM_OWN + 32);
#pragma unroll
            for (int i = 0; i < 8; i++) {
                const uint32_t c1 = (i & 4) ? cc.y : cc.x, c2 = prmt(c1, c1, (i & 2) ? 0x3232u : 0x1010u);
                stg128(G.w1s + (size_t)b * 2048 + 256 * i + 8 * lane, hmul2(w[i].x, c2), hmul2(w[i].y, c2), hmul2(w[i].z, c2), hmul2(w[i].w, c2));
            }
            __syncwarp();
            if (lane == 0) asm volatile("red.release.gpu.global.add.u32 [%0], 1;" ::"l"(&G.cnt[16 * 32]) : "memory");
        } else {
            {
                const float c0 = blo(cw), c1 = bhi(cw);
                sts32(sb + SM_SCV + vecpos(lane), pack2(__fdividef(c0, 1.f + __expf(-c0)), __fdividef(c1, 1.f + __expf(-c1))));
                if (lane == 0) sts128(sb + SM_ONE, make_uint4(0x3F803F80u, 0x3F803F80u, 0x3F803F80u, 0x3F803F80u));
            }
            bar_sync(5, 384);
            {
                const uint4 v0 = lds128(sb + SM_RED + lane * 32), v1 = lds128(sb + SM_RED + lane * 32 + 16);
                float m = (__uint_as_float(v0.x) + __uint_as_float(v0.z)) + (__uint_as_float(v1.x) + __uint_as_float(v1.z));
                float e2 = (__uint_as_float(v0.y) + __uint_as_float(v0.w)) + (__uint_as_float(v1.y) + __uint_as_float(v1.w));
                m = (m + shx(m, 1)) * (1.f / 512.f); e2 = (e2 + shx(e2, 1)) * (1.f / 512.f);
                const float r = rsq(fmaxf(fmaf(-m, m, e2), 0.f) + LN_EPS);
                if (!(lane & 1)) str32(&G.stats0[16 * b + (lane >> 1)], (pack2(-m, r) & 0x7FFFFFFFu) | (ep << 31));
            }
#pragma unroll 1
            for (int rd = 0; rd < 2; rd++) { OWNMOD(rd) }
        }
        RELANE()
        {
            mbar_wait(BAR(B_MOD + 1));
            uint4 v[2];
            for (int it = 0;; it++) {
                v[0] = ldr128(&G.modp[at]); v[1] = ldr128(&G.modp[128 + at]);
                if (!any(stale(v[0].w ^ ep, v[1].w, ep))) break;
                if (it > SPIN_MAX) __trap();
                __nanosleep(100);
            }
#pragma unroll
            for (int h = 0; h < 2; h++) {
                const uint32_t vp = sb + SM_CBV + 512 * h + ((at & 1) ? 0 : 1024) + vecpos(at & ~1);
                sts32(vp, v[h].x); sts32(vp + 16, v[h].y);
                if (4 * h + aw == cs) sts64(sb + SM_GB + 8 * lane, v[h].z << 16, v[h].z & 0xFFFF0000u);
            }
            warp_arrive(BAR(B_W1RDY));
            if (aw == 3) {
                tma2d_e(sb + SM_W1C, &M.m[tmW1c], 8 * (b >> 1), 256 * pr, BAR(B_W1C));
            }
        }
        if (aw < 2) {
            const int s = aw, tau = 16 * s + gi, c = lane & 7;
            const int sh = (c & 4 ? 2 : 1) * (c & 2 ? 1 : -1);
#pragma unroll 1
            for (int i = lane; i < 128; i += 32) stg128(G.stats1 + (tau * 8 + cs) * 128 + i, ep + 1, 0, ep + 1, 0);
            mbar_wait(BAR(B_CONV + s));
            fence_async_smem();
#pragma unroll 1
            for (int ph = 0; ph < 3; ph++) {
                const uint32_t* fp; uint32_t target = 4 * ep; bool need = lane < 8;
                if (ph == 0) { fp = &G.cnt[((tau < 18 ? 0 : 8) + c) * 32]; target = 64 * ep; }
                else if (ph == 1) {
                    const int tn = lane < 8 ? tau : tau + (sh > 0 ? 1 : -1);
                    need = lane < 16 && tn >= 0 && tn < 32;
                    fp = &G.flag[((need ? tn : tau) * 8 + c) * 32];
                } else fp = &G.flag[((32 + tau) * 8 + c) * 32];
                uint32_t m = 0xFFFFu;
#define POLL(mask) while (m & (mask)) m = __ballot_sync(0xffffffffu, need && ldr32(fp) != target);
                if (ph < 2) {
                    const uint32_t dst = sb + (s ? SM_P1 : SM_Q), fb = BAR(B_PAIR + 8 * ph + 4 * s);
                    const int c0 = ph ? 0 : 64 * tau, c1 = ph ? 64 * tau + 2 : 0;
                    const CUtensorMap* tm = &M.m[tmX2 + ph];
                    if (ph) mbar_wait(BAR(B_TILE + s));
#define FETCH(j, sh_) { const int p = ph ? (j) : ((j) + (cs >> 1)) & 3; POLL(0x0303u << (2 * p)) tma3d_e(dst + 16384 * p, tm, c0, c1 + (sh_) * ph, 2 * p, fb + 8 * p); }
                    FETCH(0, -1)
                    FETCH(1, 1) FETCH(2, -2) FETCH(3, 2)
#undef FETCH
                } else {
                    uint32_t dst = sb + SM_Q + (s ? 7 : 10) * 8192;
                    mbar_wait(BAR(B_W3F)); mbar_wait(BAR(s ? B_DST : B_TILE + 2));
#pragma unroll 1
                    for (int k = 0; k < 8; k++) {
                        if (s && k >= 3) mbar_wait(BAR(B_EMPTY + k - 3));
                        POLL(1u << k)
                        tma3d_e(dst, &M.m[tmX1], 0, 64 * tau, k, BAR(B_X1 + 8 * s + k));
                        dst = dst == sb + SM_Q + 10 * 8192 ? sb + SM_Q : dst + 8192;
                    }
                }
#undef POLL
            }
            {
                float sm[2], sq[2];
                for (;;) {
                    uint32_t bad = 0;
                    sm[0] = sm[1] = sq[0] = sq[1] = 0.f;
#pragma unroll
                    for (int k = 0; k < 8; k++) {
                        const uint4 v = ldr128(&G.stats2[2048 * k + 64 * tau + 2 * lane]);
                        bad = stale(stale(bad, v.x, ep), v.z, ep);
                        sm[0] += __uint_as_float(v.x); sq[0] += __uint_as_float(v.y); sm[1] += __uint_as_float(v.z); sq[1] += __uint_as_float(v.w);
                    }
                    mbar_wait(BAR(B_CONST));
                    if (!any(bad)) break;
                }
#pragma unroll
                for (int r = 0; r < 2; r++) {
                    const float m = sm[r] * (1.f / 512.f), r3 = rsq(fmaxf(fmaf(-m, m, sq[r] * (1.f / 512.f)), 0.f) + LN_EPS);
                    sts128(sb + SM_RED + s * 1024 + 32 * lane + 16 * r, make_uint4(fbits(GK1 * r3 * r3 * r3), fbits(GK0 * r3), fbits(0.5f * r3), split2(-m)));
                }
                warp_arrive(BAR(B_LN3 + s));
            }
            {
                uint4* pd = G.part + (size_t)((gi * 8 + 4 * pr + ((pa + 3) & 3)) * 6 + 4 + s) * 512 + lane;
#pragma unroll 1
                for (int v = 0; v < 16; v++) { stg128(pd + 32 * v, ep + 1, 0, 0, 0); __nanosleep(20); }
            }
        } else if (aw == 2) {
            mbar_wait(BAR(B_NEAR));
            while (any((ldr32(&G.cnt[16 * 32]) - 128 * ep) >> 31)) __nanosleep(100);
            asm volatile("fence.acquire.gpu;" ::: "memory");
            fence_async_global(); fence_async_smem();
            tma2d_e(sb + SM_W1, &M.m[tmW1], 64 * cs, 0, BAR(B_W1FULL));
            tma2d_e(sb + SM_W1 + 32768, &M.m[tmW1], 64 * cs, 256, BAR(B_W1FULL));
            mbar_wait(BAR(B_CONST));
            uint2 v[6];
            for (;;) {
                uint32_t bad = 0;
#pragma unroll
                for (int k = 0; k < 6; k++) { v[k] = ldr64(&G.u123[512 * k + 64 * cs + 2 * lane]); bad = stale(bad, v[k].x, ep); }
                if (!any(bad)) break;
            }
#pragma unroll
            for (int k = 0; k < 3; k++)
                sts64(sb + SM_U123 + 256 * k + 8 * lane, split2(__uint_as_float(v[k].x) + __uint_as_float(v[k + 3].x)), split2(__uint_as_float(v[k].y) + __uint_as_float(v[k + 3].y)));
            warp_arrive(BAR(B_U123));
            mbar_wait(BAR(B_WA + 1));
#pragma unroll 1
            for (int t = 0; t < 4; t++) {
                tma2d_e(sb + SM_W1 + 16384 * t, &M.m[tmW2], 64 * cs, 128 * t, BAR(B_W2FULL + t));
                mbar_wait(BAR(B_W2FULL + t));
            }
#pragma unroll 1
            for (int t = 0; t < 8; t++) {
                mbar_wait(BAR(t < 2 ? B_WFREE : t < 4 ? B_TILE + 3 : B_WEMPTY + t - 4));
                if (t && t < 4 && PACE) mbar_wait(BAR(B_WFULL + t - 1));
                if (t == 0 && !(XP & 8)) mbar_wait(BAR(B_PAIR + 15));
                if ((XP & 8) && t == 1) mbar_wait(BAR(B_PAIR + 15));
                if ((XP & 16) && t == 3) mbar_wait(BAR(B_X1 + 10));
                tma3d_e(sb + wstage(t), &M.m[tmW3], 0, 64 * t, 7 * fs, BAR(B_WFULL + t));
            }
#pragma unroll 1
            for (int j = 0; j < 8; j++) {
                const int jj = (j == 1 || j == 2) ? 3 - j : j, odd = (pr ^ jj) & 1, c0 = 64 * (4 * pr + ((pa + (jj >> 1) + 1) & 3));
                mbar_wait(BAR(B_WEMPTY + 4 + j));
                tma2d_e(sb + wstage(j), &M.m[tmW4], c0, 448 * pa + 224 * odd, BAR(B_WFULL + 8 + j));
            }
        } else {
            if (sb & 1023) __trap();
            mbar_wait_b(BAR(B_AUXQ));
            const uint4 v0 = lds128(sb + SM_ARED + 32 * lane), v1 = lds128(sb + SM_ARED + 32 * lane + 16);
            const float q0 = (__uint_as_float(v0.x) + __uint_as_float(v0.z)) + (__uint_as_float(v1.x) + __uint_as_float(v1.z));
            const float q1 = (__uint_as_float(v0.y) + __uint_as_float(v0.w)) + (__uint_as_float(v1.y) + __uint_as_float(v1.w));
            if (lane >= 16 && lane < 28) str64(&G.u123[1536 * pr + 512 * (g - 4) + 8 * (b >> 1) + 2 * q], tagf(q0, ep), fbits(q1));
            if (lane < 8) sts64(sb + SM_CONST + 8 * lane, fbits(q0), fbits(q1));
            warp_arrive(BAR(B_CONST));
            {
                float d[4] = {0.f, 0.f, 0.f, 0.f};
                if (lane == 0) mbar_expect(BAR(B_W3D), 8192);
                mbar_wait_b(BAR(B_PAIR + 4 + (((cs >> 1) + 3) & 3)));
#pragma unroll 1
                for (int h = 0; h < 2; h++) {
                    fence_async_smem();
                    tma2d_e(sb + SM_W3C, &M.m[tmW3c], 16 * b, 256 * h, BAR(h ? B_W3D : B_W3C));
                    mbar_wait_b(BAR(h ? B_W3D : B_W3C));
#pragma unroll 4
                    for (int i = 0; i < 32; i++) {
                        const uint2 w = lds64(sb + SM_W3C + i * 256 + lane * 8);
                        d[0] += blo(w.x); d[1] += bhi(w.x); d[2] += blo(w.y); d[3] += bhi(w.y);
                    }
                }
#pragma unroll
                for (int i = 0; i < 4; i++) { d[i] += shx(d[i], 4); d[i] += shx(d[i], 8); d[i] += shx(d[i], 16); }
                if (g < 2 && b < 112) str64(&G.u4[16 * b + 4 * q + 2 * g], tagf(g ? d[2] : d[0], ep), fbits(g ? d[3] : d[1]));
                warp_arrive(BAR(B_W3F));
            }
            mbar_wait_b(BAR(B_DST));
#pragma unroll 1
            for (int n = lane; n < 128; n += 32) {
                const int i = min(n, 111);
                uint2 uv; int it = 0;
                do { uv = ldr64(&G.u4[224 * fs + 2 * i]); if (++it > SPIN_MAX) __trap(); } while (any(uv.x ^ ep));
                const uint32_t v0 = split2(__uint_as_float(uv.x)), v1 = split2(__uint_as_float(uv.y));
                sts128(sb + SM_U4 + 32 * i, make_uint4(prmt(v0, v0, 0x3232u), prmt(v0, v0, 0x1010u), 0u, 0u));
                sts128(sb + SM_U4 + 32 * i + 16, make_uint4(prmt(v1, v1, 0x3232u), prmt(v1, v1, 0x1010u), 0u, 0u));
            }
            fence_async_smem();
            warp_arrive(BAR(B_U4));
            mbar_wait_b(BAR(B_DONE));
        }
    }
}

#undef G
#undef at
#undef OWNMOD

typedef CUresult (*EncodeFn)(CUtensorMap*, CUtensorMapDataType, cuuint32_t, void*, const cuuint64_t*, const cuuint64_t*,
                             const cuuint32_t*, const cuuint32_t*, CUtensorMapInterleave, CUtensorMapSwizzle,
                             CUtensorMapL2promotion, CUtensorMapFloatOOBfill);

void encode(EncodeFn fn, CUtensorMap* m, const void* base, int rank, const cuuint64_t* dim, const cuuint64_t* stride,
            const cuuint32_t* box, CUtensorMapSwizzle sw) {
    const cuuint32_t es[5] = {1, 1, 1, 1, 1};
    fn(m, CU_TENSOR_MAP_DATA_TYPE_BFLOAT16, rank, const_cast<void*>(base), dim, stride, box, es, CU_TENSOR_MAP_INTERLEAVE_NONE,
       sw, CU_TENSOR_MAP_L2_PROMOTION_L2_128B, CU_TENSOR_MAP_FLOAT_OOB_FILL_NONE);
}

}

extern "C" void kernel_launch(void* const* d_in, const int* in_sizes, int n_in, void* d_out, int out_size) {
    (void)in_sizes; (void)n_in; (void)out_size;
    Params P;
    P.x = (const bf16*)d_in[0]; P.Are = (const bf16*)d_in[1]; P.Aim = (const bf16*)d_in[2]; P.Bre = (const bf16*)d_in[3];
    P.Bim = (const bf16*)d_in[4]; P.Cre = (const bf16*)d_in[5]; P.Cim = (const bf16*)d_in[6]; P.logdt = (const bf16*)d_in[7];
    P.dskip = (const bf16*)d_in[8]; P.w1 = (const bf16*)d_in[10]; P.w2 = (const bf16*)d_in[11]; P.w3 = (const bf16*)d_in[12];
    P.w4 = (const bf16*)d_in[13]; P.c = (const bf16*)d_in[14]; P.wmod = (const bf16*)d_in[15]; P.out = (bf16*)d_out;

    void* fnp = nullptr;
    cudaDriverEntryPointQueryResult qr;
    cudaGetDriverEntryPoint("cuTensorMapEncodeTiled", &fnp, cudaEnableDefault, &qr);
    EncodeFn fn = (EncodeFn)fnp;
    cudaFuncSetAttribute(fused_kernel, cudaFuncAttributeMaxDynamicSharedMemorySize, SM_TOTAL);
    void* pgs;
    cudaGetSymbolAddress(&pgs, g_scratch);
    Scratch* gs = P.gs = (Scratch*)pgs;
    const void *px2 = gs->x2t, *pg = gs->g, *px1 = gs->x1;
    Maps M;
    { const cuuint64_t d[3] = {2048, 64, 8}, st[2] = {4096, 64 * 4096}; const cuuint32_t bx[3] = {64, 64, 2}; encode(fn, &M.m[tmX2], px2, 3, d, st, bx, CU_TENSOR_MAP_SWIZZLE_128B); }
    { const cuuint64_t d[3] = {64, 2052, 8}, st[2] = {1024, 128}; const cuuint32_t bx[3] = {64, 64, 2}; encode(fn, &M.m[tmG], pg, 3, d, st, bx, CU_TENSOR_MAP_SWIZZLE_128B); }
    { const cuuint64_t d[3] = {64, 2048, 8}, st[2] = {1024, 128}; const cuuint32_t bx[3] = {64, 64, 1}; encode(fn, &M.m[tmX1], px1, 3, d, st, bx, CU_TENSOR_MAP_SWIZZLE_128B); }
    { const cuuint64_t d[2] = {512, 512}, st[1] = {1024}; const cuuint32_t bx[2] = {64, 256}, bc[2] = {8, 256};
      encode(fn, &M.m[tmW1], gs->w1s, 2, d, st, bx, CU_TENSOR_MAP_SWIZZLE_128B); encode(fn, &M.m[tmW1c], P.w1, 2, d, st, bc, CU_TENSOR_MAP_SWIZZLE_NONE); }
    { const cuuint64_t d[2] = {512, 512}, st[1] = {1024}; const cuuint32_t bx[2] = {64, 128}; encode(fn, &M.m[tmW2], P.w2, 2, d, st, bx, CU_TENSOR_MAP_SWIZZLE_128B); }
    { const cuuint64_t d[3] = {32, 512, 56}, st[2] = {3584, 64}; const cuuint32_t bx[3] = {32, 64, 7}; encode(fn, &M.m[tmW3], P.w3, 3, d, st, bx, CU_TENSOR_MAP_SWIZZLE_64B); }
    { const cuuint64_t d[2] = {512, 1792}, st[1] = {1024}; const cuuint32_t bx[2] = {64, 224}; encode(fn, &M.m[tmW4], P.w4, 2, d, st, bx, CU_TENSOR_MAP_SWIZZLE_128B); }
    { const cuuint64_t d[2] = {512, 2048}, st[1] = {1024}; const cuuint32_t bx[2] = {8, 256}; encode(fn, &M.m[tmXc], P.x, 2, d, st, bx, CU_TENSOR_MAP_SWIZZLE_NONE); }
    { const cuuint64_t d[2] = {3072, 512}, st[1] = {6144}; const cuuint32_t bx[2] = {64, 64}; encode(fn, &M.m[tmWm], P.wmod, 2, d, st, bx, CU_TENSOR_MAP_SWIZZLE_128B); }
    { const cuuint64_t d[2] = {1792, 512}, st[1] = {3584}; const cuuint32_t bx[2] = {16, 256}; encode(fn, &M.m[tmW3c], P.w3, 2, d, st, bx, CU_TENSOR_MAP_SWIZZLE_NONE); }

    fused_kernel<<<128, 384, SM_TOTAL, cudaStreamPerThread>>>(P, M);
}
```
